```python
import torch

def _softmax(x, axis=-1):
    return torch.softmax(x, dim=axis)
def _gelu(x):
    return torch.nn.functional.gelu(x, approximate="tanh")
def _silu(x):
    return torch.nn.functional.silu(x)
def _sigmoid(x):
    return torch.sigmoid(x)
def _layernorm(x, axis=-1, eps=1e-5):
    m = x.mean(dim=axis, keepdim=True)
    v = x.var(dim=axis, keepdim=True, unbiased=False)
    return (x - m) / torch.sqrt(v + eps)
def _scatter_add(tgt, idx, src, axis=0):
    return tgt.clone().index_add_(axis, idx, src)
def _segment_sum(src, seg, n):
    out = torch.zeros((n,) + src.shape[1:], dtype=src.dtype)
    return out.index_add_(0, seg, src)
def _pad(x, pw):
    flat = tuple(v for pair in reversed(pw) for v in pair)
    return torch.nn.functional.pad(x, flat)

kernel_name = 'sequential_preLN__mha_block_cached__geglu_ffn__decode'

def setup_inputs():

    _w = (lambda a: (lambda t: t.to(torch.bfloat16) if t.is_floating_point() else t)(torch.as_tensor(a)))
    def _A_setup():
        B, Sq, D = 2, 1, 1024
        H, Sk, Dh = 32, 16384, 128
        return {
            "x": _w((lambda *s: torch.randn(*s, dtype=torch.bfloat16) * 0.05)(B, Sq, D)),
            "k_cache": _w((lambda *s: torch.randn(*s, dtype=torch.bfloat16) * 3.2)(B, H, Sk, Dh)),
            "v_cache": _w((lambda *s: torch.randn(*s, dtype=torch.bfloat16) * 0.4)(B, H, Sk, Dh)),
            "wq": _w((lambda *s: torch.randn(*s, dtype=torch.bfloat16) * 3.2)(D, H * Dh) * (D ** -0.5)),
            "wo": _w((lambda *s: torch.randn(*s, dtype=torch.bfloat16) * 0.4)(H * Dh, D) * ((H * Dh) ** -0.5)),
        }
    _A_in = _A_setup()

    def _B_setup():
        B, S, D, F = 2, 1, 1024, 3584
        return {
            "x": _w((lambda *s: torch.randn(*s, dtype=torch.bfloat16) * 0.05)(B, S, D)),
            "w_gate": _w((lambda *s: torch.randn(*s, dtype=torch.bfloat16) * 0.05)(D, F)),
            "w_up": _w((lambda *s: torch.randn(*s, dtype=torch.bfloat16) * 0.05)(D, F)),
            "w_down": _w((lambda *s: torch.randn(*s, dtype=torch.bfloat16) * 0.05)(F, D)),
        }
    _B_in = _B_setup()

    return {
        "A_x": _A_in["x"],
        "A_k_cache": _A_in["k_cache"],
        "A_v_cache": _A_in["v_cache"],
        "A_wq": _A_in["wq"],
        "A_wo": _A_in["wo"],
        "B_x": _B_in["x"],
        "B_w_gate": _B_in["w_gate"],
        "B_w_up": _B_in["w_up"],
        "B_w_down": _B_in["w_down"],
    }

def reference(A_x, A_k_cache, A_v_cache, A_wq, A_wo, B_x, B_w_gate, B_w_up, B_w_down):
    def _A_ref(x, k_cache, v_cache, wq, wo):
        B, Sq, D = x.shape
        H, Dh = 32, 128
        q = (lambda x, *d: x.permute(*d))((x @ wq).reshape(B, Sq, H, Dh), 0, 2, 1, 3)
        scores = torch.einsum("bhqd,bhkd->bhqk", q, k_cache) * (Dh ** -0.5)
        p = _softmax(scores, axis=-1)
        o = torch.einsum("bhqk,bhkd->bhqd", p, v_cache)
        return (lambda x, *d: x.permute(*d))(o, 0, 2, 1, 3).reshape(B, Sq, H * Dh) @ wo

    def _B_ref(x, w_gate, w_up, w_down):
        return (_gelu(x @ w_gate) * (x @ w_up)) @ w_down

    x = A_x
    h = x + _A_ref(_layernorm(x, axis=-1), A_k_cache, A_v_cache, A_wq, A_wo)
    h2 = h + _B_ref(_layernorm(h, axis=-1), B_w_gate, B_w_up, B_w_down)
    return h2
```

```cpp
#include <cuda_runtime.h>
#include <cuda_bf16.h>
#include <cuda.h>
#include <stdint.h>

namespace {

constexpr int kD = 1024, kH = 32, kSK = 16384, kDH = 128, kF = 3584;
constexpr int kG = 128;
constexpr int kFFN = kF / 32;
constexpr int kFG = kFFN / 4;
constexpr int kNST = 6;
constexpr int kStage = 32768;
constexpr int kUnit = 8192;
constexpr int kTileKeys = 64;
constexpr int kHalfTiles = 128;
constexpr int kStaticTiles = 96;
constexpr int kLevels = 6;
constexpr int kTickets = kLevels * kG;
constexpr int kSlots = kLevels + 1;
constexpr int kPartStride = 132;
#define CAPU_KV 5
#define CAPU_ST 8
#define CAPU_WO 4
#define CAPU_GU 4
#define CAPU_DN 5
constexpr int kCapST = CAPU_ST;
constexpr int kCapKV = CAPU_KV;
constexpr int kCapWO = CAPU_WO, kCapGU = CAPU_GU, kCapDN = CAPU_DN;
#define CAPU_START 5
constexpr int kCapStart = CAPU_START;
constexpr int kThreads = 160;
constexpr float kLog2e = 1.4426950408889634f;
constexpr int kSpinLimit = 1 << 22;

constexpr int SM_QALL = kNST * kStage;
constexpr int SM_HN = SM_QALL;
constexpr int SM_RBUF = SM_QALL + 8192;
constexpr int SM_OS = SM_QALL + 12288;
constexpr int SM_ACT = SM_QALL + 12800;
constexpr int SM_FLUSH = SM_QALL + 16384;
constexpr int SM_XN = SM_FLUSH;
constexpr int SM_RBUF0 = SM_FLUSH + 4096;
constexpr int SM_STATS = SM_FLUSH + 16 * 136 * 4;
constexpr int SM_LNRED = SM_STATS + 64;
constexpr int SM_RED2 = SM_LNRED + 64;
constexpr int SM_BARS = SM_RED2 + 512;
constexpr int SM_META = SM_BARS + 5 * kNST * 8;
constexpr int SM_TOTAL = SM_META + 64;
constexpr int kSmemBytes = SM_TOTAL + 1024;

struct Scratch {
  unsigned epoch, tagprev; unsigned pad0[30];
  unsigned ticket;         unsigned pad1[31];
  uint32_t qp[2 * 2 * kH * kDH];
  uint32_t q[2 * kH * kDH];
  uint32_t hfin[2 * kD];
  uint32_t gp[kFFN * 4 * 64];
  uint32_t part[kG * kSlots * kPartStride];
  uint32_t hll[kG * kH * 16];
  uint32_t oll[kG * kFG * 16];
};
__device__ Scratch g_s;

#define STAMP(i)
#define PSTAMP(i)

__device__ __forceinline__ uint32_t smem_u32(const void* p) { return (uint32_t)__cvta_generic_to_shared(p); }
__device__ __forceinline__ void mbar_init(uint32_t bar, uint32_t cnt) {
  asm volatile("mbarrier.init.shared::cta.b64 [%0], %1;" ::"r"(bar), "r"(cnt) : "memory");
}
__device__ __forceinline__ void mbar_expect_tx(uint32_t bar, uint32_t bytes) {
  asm volatile("mbarrier.arrive.expect_tx.shared::cta.b64 _, [%0], %1;" ::"r"(bar), "r"(bytes) : "memory");
}
__device__ __forceinline__ void mbar_arrive(uint32_t bar) {
  asm volatile("mbarrier.arrive.shared::cta.b64 _, [%0];" ::"r"(bar) : "memory");
}
__device__ __forceinline__ bool mbar_try(uint32_t bar, uint32_t parity) {
  uint32_t ok;
  asm volatile("{\n.reg .pred p;\nmbarrier.try_wait.parity.shared::cta.b64 p, [%1], %2;\nselp.u32 %0, 1, 0, p;\n}"
               : "=r"(ok) : "r"(bar), "r"(parity) : "memory");
  return ok;
}
__device__ __forceinline__ void mbar_wait(uint32_t bar, uint32_t parity) {
  if (mbar_try(bar, parity)) return;
  for (int it = 0; it < (1 << 24); ++it)
    if (mbar_try(bar, parity)) return;
  __trap();
}
__device__ __forceinline__ void bulk_load(uint32_t dst, const void* src, uint32_t bytes, uint32_t bar, uint64_t pol) {
  asm volatile("cp.async.bulk.shared::cluster.global.mbarrier::complete_tx::bytes.L2::cache_hint [%0], [%1], %2, [%3], %4;"
               ::"r"(dst), "l"(src), "r"(bytes), "r"(bar), "l"(pol) : "memory");
}
__device__ __forceinline__ void tma2d(uint32_t dst, const CUtensorMap* map, int c0, int c1, uint32_t bar) {
  asm volatile("cp.async.bulk.tensor.2d.shared::cluster.global.mbarrier::complete_tx::bytes [%0], [%1, {%3, %4}], [%2];"
               ::"r"(dst), "l"(map), "r"(bar), "r"(c0), "r"(c1) : "memory");
}
__device__ __forceinline__ void prefetch_map(const CUtensorMap* map) {
  asm volatile("prefetch.tensormap [%0];" ::"l"(map) : "memory");
}
__device__ __forceinline__ void cbar() { asm volatile("bar.sync 1, 128;" ::: "memory"); }
__device__ __forceinline__ uint32_t ld_ll1(const uint32_t* p) {
  uint32_t v;
  asm volatile("ld.relaxed.gpu.global.u32 %0, [%1];" : "=r"(v) : "l"(p) : "memory");
  return v;
}
__device__ __forceinline__ uint2 ld_ll2(const uint32_t* p) {
  uint2 v;
  asm volatile("ld.relaxed.gpu.global.v2.u32 {%0, %1}, [%2];" : "=r"(v.x), "=r"(v.y) : "l"(p) : "memory");
  return v;
}
__device__ __forceinline__ uint4 ld_ll4(const uint32_t* p) {
  uint4 v;
  asm volatile("ld.relaxed.gpu.global.v4.u32 {%0, %1, %2, %3}, [%4];" : "=r"(v.x), "=r"(v.y), "=r"(v.z), "=r"(v.w) : "l"(p) : "memory");
  return v;
}
__device__ __forceinline__ void st_ll1(uint32_t* p, uint32_t a) {
  asm volatile("st.relaxed.gpu.global.u32 [%0], %1;" ::"l"(p), "r"(a) : "memory");
}
__device__ __forceinline__ void st_ll2(uint32_t* p, uint32_t a, uint32_t b) {
  asm volatile("st.relaxed.gpu.global.v2.u32 [%0], {%1, %2};" ::"l"(p), "r"(a), "r"(b) : "memory");
}
__device__ __forceinline__ uint32_t tag32(float v, uint32_t tag) { return (__float_as_uint(v) & ~3u) | tag; }
__device__ __forceinline__ float untag32(uint32_t w) { return __uint_as_float(w & ~3u); }
__device__ __forceinline__ uint32_t tag16(float v, uint32_t tag) {
  return ((uint32_t)__bfloat16_as_ushort(__float2bfloat16_rn(v)) << 16) | tag;
}
__device__ __forceinline__ float untag16(uint32_t w) { return __uint_as_float(w & 0xffff0000u); }
__device__ __forceinline__ uint32_t pack16(uint32_t lo, uint32_t hi) { return __byte_perm(lo, hi, 0x7632); }
__device__ __forceinline__ bool ok4(const uint4& v, uint32_t tag) {
  return (((v.x ^ tag) | (v.y ^ tag) | (v.z ^ tag) | (v.w ^ tag)) & 3u) == 0;
}
__device__ __forceinline__ void ldsm4(uint32_t (&a)[4], uint32_t addr) {
  asm volatile("ldmatrix.sync.aligned.m8n8.x4.shared.b16 {%0,%1,%2,%3}, [%4];"
               : "=r"(a[0]), "=r"(a[1]), "=r"(a[2]), "=r"(a[3]) : "r"(addr) : "memory");
}
__device__ __forceinline__ void ldsm4t(uint32_t (&a)[4], uint32_t addr) {
  asm volatile("ldmatrix.sync.aligned.m8n8.x4.trans.shared.b16 {%0,%1,%2,%3}, [%4];"
               : "=r"(a[0]), "=r"(a[1]), "=r"(a[2]), "=r"(a[3]) : "r"(addr) : "memory");
}
__device__ __forceinline__ void mma16816(float (&c)[4], const uint32_t (&a)[4], uint32_t b0, uint32_t b1) {
  asm("mma.sync.aligned.m16n8k16.row.col.f32.bf16.bf16.f32 {%0,%1,%2,%3}, {%4,%5,%6,%7}, {%8,%9}, {%0,%1,%2,%3};"
               : "+f"(c[0]), "+f"(c[1]), "+f"(c[2]), "+f"(c[3])
               : "r"(a[0]), "r"(a[1]), "r"(a[2]), "r"(a[3]), "r"(b0), "r"(b1));
}
__device__ __forceinline__ float bf16r(float x) { return __bfloat162float(__float2bfloat16_rn(x)); }
__device__ __forceinline__ float ex2(float x) {
  float y;
  asm("ex2.approx.ftz.f32 %0, %1;" : "=f"(y) : "f"(x));
  return y;
}
__device__ __forceinline__ float rcp(float x) {
  float y;
  asm("rcp.approx.ftz.f32 %0, %1;" : "=f"(y) : "f"(x));
  return y;
}
__device__ __forceinline__ float warp_sum(float v) {
#pragma unroll
  for (int o = 16; o > 0; o >>= 1) v += __shfl_xor_sync(0xffffffffu, v, o);
  return v;
}
__device__ __forceinline__ float warp_max_redux(float v) {
  int k = __float_as_int(v);
  k ^= (k >> 31) & 0x7fffffff;
  k = __reduce_max_sync(0xffffffffu, k);
  k ^= (k >> 31) & 0x7fffffff;
  return __int_as_float(k);
}
__device__ __forceinline__ uint32_t lds32(uint32_t addr) {
  uint32_t v;
  asm volatile("ld.shared.u32 %0, [%1];" : "=r"(v) : "r"(addr) : "memory");
  return v;
}

__device__ __forceinline__ void layernorm2(const float (&v)[2][8], uint8_t* dst, float* red, int tid, int col) {
  const int lane = tid & 31, warp = tid >> 5;
  float mu[2], m2[2];
#pragma unroll
  for (int b = 0; b < 2; ++b) {
    mu[b] = (((v[b][0] + v[b][1]) + (v[b][2] + v[b][3])) + ((v[b][4] + v[b][5]) + (v[b][6] + v[b][7]))) * 0.125f;
    float q0 = 0.f, q1 = 0.f;
#pragma unroll
    for (int i = 0; i < 4; ++i) {
      const float d0 = v[b][i] - mu[b], d1 = v[b][4 + i] - mu[b];
      q0 = fmaf(d0, d0, q0); q1 = fmaf(d1, d1, q1);
    }
    m2[b] = q0 + q1;
  }
  float wgt = 4.0f;
#pragma unroll
  for (int o = 1; o < 32; o <<= 1) {
#pragma unroll
    for (int b = 0; b < 2; ++b) {
      const float mo = __shfl_xor_sync(0xffffffffu, mu[b], o), qo = __shfl_xor_sync(0xffffffffu, m2[b], o);
      const float d = mo - mu[b];
      m2[b] = fmaf(d * d, wgt, m2[b] + qo);
      mu[b] = 0.5f * (mu[b] + mo);
    }
    wgt *= 2.0f;
  }
  if (lane == 0) *reinterpret_cast<float4*>(red + warp * 4) = make_float4(mu[0], m2[0], mu[1], m2[1]);
  cbar();
  const float4 r0 = *reinterpret_cast<const float4*>(red), r1 = *reinterpret_cast<const float4*>(red + 4);
  const float4 r2 = *reinterpret_cast<const float4*>(red + 8), r3 = *reinterpret_cast<const float4*>(red + 12);
  float mb[2], rden[2];
  {
    const float a0 = 0.5f * (r0.x + r1.x), a1 = 0.5f * (r2.x + r3.x), d0 = r1.x - r0.x, d1 = r3.x - r2.x, d2 = a1 - a0;
    const float q = (r0.y + r1.y + 128.f * d0 * d0) + (r2.y + r3.y + 128.f * d1 * d1) + 256.f * d2 * d2;
    mb[0] = bf16r(0.5f * (a0 + a1));
    rden[0] = 1.0f / bf16r(sqrtf(bf16r(bf16r(q * (1.0f / kD)) + 1e-5f)));
  }
  {
    const float a0 = 0.5f * (r0.z + r1.z), a1 = 0.5f * (r2.z + r3.z), d0 = r1.z - r0.z, d1 = r3.z - r2.z, d2 = a1 - a0;
    const float q = (r0.w + r1.w + 128.f * d0 * d0) + (r2.w + r3.w + 128.f * d1 * d1) + 256.f * d2 * d2;
    mb[1] = bf16r(0.5f * (a0 + a1));
    rden[1] = 1.0f / bf16r(sqrtf(bf16r(bf16r(q * (1.0f / kD)) + 1e-5f)));
  }
#pragma unroll
  for (int b = 0; b < 2; ++b) {
#pragma unroll
    for (int k = 0; k < 2; ++k) {
      const __nv_bfloat162 dl = __floats2bfloat162_rn(v[b][4 * k] - mb[b], v[b][4 * k + 1] - mb[b]);
      const __nv_bfloat162 dh = __floats2bfloat162_rn(v[b][4 * k + 2] - mb[b], v[b][4 * k + 3] - mb[b]);
      const __nv_bfloat162 lo = __floats2bfloat162_rn(__low2float(dl) * rden[b], __high2float(dl) * rden[b]);
      const __nv_bfloat162 hi = __floats2bfloat162_rn(__low2float(dh) * rden[b], __high2float(dh) * rden[b]);
      *reinterpret_cast<uint2*>(dst + b * (kD * 2) + k * 1024 + col * 8) =
          make_uint2(*reinterpret_cast<const uint32_t*>(&lo), *reinterpret_cast<const uint32_t*>(&hi));
    }
  }
  cbar();
}

__device__ __forceinline__ void gemv_box64(float (&acc)[4][4], uint32_t box, const uint32_t* b, int lane) {
  const int li = lane & 7, lj = lane >> 3;
  const uint32_t row = box + (li + 8 * (lj >> 1)) * 128;
  uint32_t a[4][4][4];
#pragma unroll
  for (int s = 0; s < 4; ++s) {
#pragma unroll
    for (int mt = 0; mt < 4; ++mt)
      ldsm4t(a[s][mt], row + s * 2048 + ((((uint32_t)(2 * mt + (lj & 1))) ^ (uint32_t)li) << 4));
  }
#pragma unroll
  for (int s = 0; s < 4; ++s) {
#pragma unroll
    for (int mt = 0; mt < 4; ++mt) mma16816(acc[mt], a[s][mt], b[2 * s], b[2 * s + 1]);
  }
}

__device__ __forceinline__ void load_bfrag(uint32_t (&b)[16], uint32_t addr) {
#pragma unroll
  for (int s = 0; s < 16; ++s) b[s] = lds32(addr + s * 16);
}

__device__ __forceinline__ void store_acc64(float* dst, const float (&acc)[4][4], int g, int t) {
  if (t < 2) {
#pragma unroll
    for (int mt = 0; mt < 4; ++mt)
      *reinterpret_cast<float2*>(dst + (16 * mt + 8 * t + g) * 2) =
          t == 0 ? make_float2(acc[mt][0], acc[mt][1]) : make_float2(acc[mt][2], acc[mt][3]);
  }
}

template <int NSRC>
__device__ __forceinline__ void ll_send64(uint32_t* buf, int n0, int src, const float (&acc)[4][4], uint32_t tag, int g, int t) {
  if (t < 2) {
#pragma unroll
    for (int mt = 0; mt < 4; ++mt) {
      const float v0 = t == 0 ? acc[mt][0] : acc[mt][2], v1 = t == 0 ? acc[mt][1] : acc[mt][3];
      st_ll2(buf + ((n0 / 8 + 2 * mt + t) * NSRC + src) * 16 + g * 2, tag32(v0, tag), tag32(v1, tag));
    }
  }
}

template <int NSRC>
__device__ __forceinline__ float ll_reduce(const uint32_t* buf, uint4 w, uint32_t tag, float* red, int tid) {
  const int lane = tid & 31, warp = tid >> 5;
  float s[4] = {0.f, 0.f, 0.f, 0.f};
  if (tid < NSRC * 4) {
    for (int it = 0; !ok4(w, tag); ++it) {
      w = ld_ll4(buf + tid * 4);
      if (it > kSpinLimit) __trap();
    }
    s[0] = untag32(w.x); s[1] = untag32(w.y); s[2] = untag32(w.z); s[3] = untag32(w.w);
  }
#pragma unroll
  for (int o = 4; o <= 16; o <<= 1) {
#pragma unroll
    for (int e = 0; e < 4; ++e) s[e] += __shfl_xor_sync(0xffffffffu, s[e], o);
  }
  if (lane < 4) *reinterpret_cast<float4*>(red + warp * 16 + lane * 4) = make_float4(s[0], s[1], s[2], s[3]);
  cbar();
  float r = 0.f;
  if (tid < 16) r = (red[tid] + red[16 + tid]) + (red[32 + tid] + red[48 + tid]);
  return r;
}

struct Ring {
  int slot; uint32_t par;
  __device__ __forceinline__ void next() { if (++slot == kNST) { slot = 0; par ^= 1; } }
};

__global__ void __launch_bounds__(kThreads, 1)
fused_decode_kernel(const __grid_constant__ CUtensorMap map_wq, const __grid_constant__ CUtensorMap map_wo,
                    const __grid_constant__ CUtensorMap map_wg, const __grid_constant__ CUtensorMap map_wu,
                    const __grid_constant__ CUtensorMap map_wd,
                    const __nv_bfloat16* __restrict__ x, const __nv_bfloat16* __restrict__ kc,
                    const __nv_bfloat16* __restrict__ vc, __nv_bfloat16* __restrict__ out) {
  extern __shared__ uint8_t smem_raw[];
  uint8_t* smem = reinterpret_cast<uint8_t*>((reinterpret_cast<uintptr_t>(smem_raw) + 1023) & ~(uintptr_t)1023);
  const uint32_t sb = smem_u32(smem);
  const int tid = threadIdx.x, lane = tid & 31, warp = tid >> 5;
  const int c = blockIdx.x;
  const uint32_t full0 = sb + SM_BARS, empty0 = sb + SM_BARS + 4 * kNST * 8;
  volatile uint32_t* meta = reinterpret_cast<volatile uint32_t*>(smem + SM_META);

  PSTAMP(0);
  const unsigned epoch = ld_ll1(&g_s.epoch);
  const uint32_t tag = ld_ll1(&g_s.tagprev) % 3u + 1u;
  if (tid == 128) {
    prefetch_map(&map_wq);
#pragma unroll
    for (int s = 0; s < kNST; ++s) {
      mbar_init(empty0 + 8 * s, 4);
#pragma unroll
      for (int j = 0; j < 4; ++j) mbar_init(full0 + 32 * s + 8 * j, 1);
    }
    asm volatile("fence.mbarrier_init.release.cluster;" ::: "memory");
    asm volatile("fence.proxy.async.shared::cta;" ::: "memory");
  }
  __syncthreads();

  if (warp == 4) {
    if (lane == 0) {
      uint64_t pol;
      asm volatile("createpolicy.fractional.L2::evict_first.b64 %0, 1.0;" : "=l"(pol));
      int slot = 0;
      int i = 0;
      Ring wt{0, 0};
      int waited = 0;
      int u = 0;
      uint32_t lbar = 0, lpar = 0;
      int landed = 0;
      auto begin_stage = [&]() {
        while (waited < i - kNST + 1) { mbar_wait(empty0 + 8 * wt.slot, wt.par); wt.next(); ++waited; }
      };
      auto pace = [&](int cap) {
        while (landed < u - cap + 1) {
          mbar_wait(full0 + lbar, lpar);
          lbar += 8; if (lbar == 32 * kNST) { lbar = 0; lpar ^= 1; }
          ++landed;
        }
        ++u;
      };
      auto begin_unit = [&](int j, int cap) -> uint32_t {
        pace(cap);
        const uint32_t bar = full0 + 32 * slot + 8 * j;
        mbar_expect_tx(bar, kUnit);
        return bar;
      };
      auto end_stage = [&]() { ++i; if (++slot == kNST) slot = 0; };
#pragma unroll 1
      for (int j = 0; j < 8; ++j) {
        const uint32_t bar = begin_unit(j & 3, kCapStart);
        tma2d(sb + slot * kStage + (j & 3) * kUnit, &map_wq, 64 * (c >> 1), 512 * (c & 1) + 64 * j, bar);
        if ((j & 3) == 3) end_stage();
      }
      const unsigned tbase = epoch * (unsigned)(kTickets + kG);
      int hp = c, start = 0, len = kStaticTiles, level = 0;
      bool first_chunk = true;
      unsigned nxt = 0;
      while (true) {
        const int h = hp >> 2, b = (hp >> 1) & 1, half = hp & 1;
        const size_t base = ((size_t)(b * kH + h) * kSK + (size_t)(half * kHalfTiles + start) * kTileKeys) * kDH;
        const char* ksrc = reinterpret_cast<const char*>(kc + base);
        const char* vsrc = reinterpret_cast<const char*>(vc + base);
        const int cap = level == 0 ? kCapST : kCapKV;
#pragma unroll 1
        for (int tt = 0; tt < len; ++tt) {
          uint32_t m = (uint32_t)(b * kH + h) | ((uint32_t)(hp * kSlots + level) << 8);
          if (tt == 0) m |= 1u << 24;
          if (tt == len - 1) m |= 1u << 25;
          begin_stage();
          const uint32_t dst = sb + slot * kStage;
          uint32_t bar;
          {
            meta[slot] = m;
            bar = begin_unit(0, cap); bulk_load(dst, ksrc, kUnit, bar, pol);
            bar = begin_unit(1, cap); bulk_load(dst + kUnit, ksrc + kUnit, kUnit, bar, pol);
          }
          bar = begin_unit(2, cap); bulk_load(dst + 2 * kUnit, vsrc, kUnit, bar, pol);
          bar = begin_unit(3, cap); bulk_load(dst + 3 * kUnit, vsrc + kUnit, kUnit, bar, pol);
          if (first_chunk) { nxt = atomicAdd(&g_s.ticket, 1u) - tbase; first_chunk = false; }
          ksrc += 2 * kUnit; vsrc += 2 * kUnit;
          end_stage();
        }
        if (nxt >= (unsigned)kTickets) break;
        const int lv = (int)(nxt >> 7);
        hp = (int)(nxt & 127);
        level = lv + 1;
        len = lv >= 4 ? 1 : (16 >> lv);
        start = lv == 5 ? 127 : (kHalfTiles - (32 >> lv));
        nxt = atomicAdd(&g_s.ticket, 1u) - tbase;
      }
      PSTAMP(16);
      begin_stage();
      meta[slot] = 1u << 26;
#pragma unroll 1
      for (int j = 0; j < 4; ++j) { pace(64); mbar_arrive(full0 + 32 * slot + 8 * j); }
      end_stage();
      prefetch_map(&map_wo); prefetch_map(&map_wg); prefetch_map(&map_wu); prefetch_map(&map_wd);
#pragma unroll 1
      for (int j = 0; j < 8; ++j) {
        if ((j & 3) == 0) begin_stage();
        const uint32_t bar = begin_unit(j & 3, kCapWO);
        tma2d(sb + slot * kStage + (j & 3) * kUnit, &map_wo, 256 * (c & 3) + 64 * (j & 3), 128 * (c >> 2) + 64 * (j >> 2), bar);
        if ((j & 3) == 3) end_stage();
      }
      PSTAMP(17);
      if (c < kFFN) {
#pragma unroll 1
        for (int j = 0; j < 16; ++j) {
          if ((j & 3) == 0) begin_stage();
          const uint32_t bar = begin_unit(j & 3, kCapGU);
          tma2d(sb + slot * kStage + (j & 3) * kUnit, (j & 2) ? &map_wu : &map_wg, 64 * (c >> 1),
                512 * (c & 1) + 128 * (j >> 2) + 64 * (j & 1), bar);
          if ((j & 3) == 3) end_stage();
        }
        PSTAMP(18);
#pragma unroll 1
        for (int j = 0; j < 8; ++j) {
          if ((j & 3) == 0) begin_stage();
          const uint32_t bar = begin_unit(j & 3, kCapDN);
          tma2d(sb + slot * kStage + (j & 3) * kUnit, &map_wd, 256 * (c & 3) + 64 * (j & 3), 128 * (c >> 2) + 64 * (j >> 2), bar);
          if ((j & 3) == 3) end_stage();
        }
        PSTAMP(19);
      }
    }
    return;
  }

  const int g = lane >> 2, t = lane & 3;
  const int li = lane & 7, lj = lane >> 3;
  const int h_own = c >> 2, r_own = c & 3;
  const int lncol = (tid + 8 * c) & 127;

  float xres = 0.f;
  if (tid < 16) xres = __bfloat162float(x[(tid & 1) * kD + 8 * c + (tid >> 1)]);
  {
    float v[2][8];
#pragma unroll
    for (int b = 0; b < 2; ++b) {
#pragma unroll
      for (int k = 0; k < 2; ++k) {
        const uint2 pk = *reinterpret_cast<const uint2*>(x + b * kD + k * 512 + lncol * 4);
        v[b][4 * k] = __uint_as_float(pk.x << 16);     v[b][4 * k + 1] = __uint_as_float(pk.x & 0xffff0000u);
        v[b][4 * k + 2] = __uint_as_float(pk.y << 16); v[b][4 * k + 3] = __uint_as_float(pk.y & 0xffff0000u);
      }
    }
    layernorm2(v, smem + SM_XN, reinterpret_cast<float*>(smem + SM_LNRED), tid, lncol);
  }
  STAMP(10);
  Ring cs{0, 0};
  {
    float acc[4][4] = {};
    uint32_t bfr[16];
    load_bfrag(bfr, sb + SM_XN + (g & 1) * (kD * 2) + (512 * (c & 1) + 128 * warp) * 2 + t * 4);
    mbar_wait(full0 + 16 * warp, 0);
    STAMP(11);
    gemv_box64(acc, sb + warp * 16384, bfr, lane);
    mbar_wait(full0 + 16 * warp + 8, 0);
    gemv_box64(acc, sb + warp * 16384 + kUnit, bfr + 8, lane);
    __syncwarp();
    if (lane == 0) { mbar_arrive(empty0); mbar_arrive(empty0 + 8); }
    store_acc64(reinterpret_cast<float*>(smem + SM_RBUF0) + warp * 128, acc, g, t);
    cbar();
    {
      const float* r0 = reinterpret_cast<const float*>(smem + SM_RBUF0) + (tid & 63) * 2 + (tid >> 6);
      const float s = (r0[0] + r0[128]) + (r0[256] + r0[384]);
      st_ll1(g_s.qp + ((c & 1) * 2 + (tid >> 6)) * (kH * kDH) + 64 * (c >> 1) + (tid & 63), tag32(s, tag));
    }
    STAMP(12);
    if (warp == 0) {
      const int qo = ((c >> 1) & 1) * (kH * kDH) + h_own * kDH + 4 * lane;
      for (int it = 0;; ++it) {
        const uint4 w0 = ld_ll4(g_s.qp + qo), w1 = ld_ll4(g_s.qp + 2 * kH * kDH + qo);
        if (ok4(w0, tag) && ok4(w1, tag)) {
          const uint32_t q0 = tag16(untag32(w0.x) + untag32(w1.x), tag), q1 = tag16(untag32(w0.y) + untag32(w1.y), tag);
          const uint32_t q2 = tag16(untag32(w0.z) + untag32(w1.z), tag), q3 = tag16(untag32(w0.w) + untag32(w1.w), tag);
          *reinterpret_cast<uint2*>(smem + SM_QALL + qo * 2) = make_uint2(pack16(q0, q1), pack16(q2, q3));
          if ((c & 1) == 0) { st_ll2(g_s.q + qo, q0, q1); st_ll2(g_s.q + qo + 2, q2, q3); }
          break;
        }
        if (it > kSpinLimit) __trap();
      }
    }
    cbar();
    cs.next(); cs.next();
  }
  STAMP(1);

  {
    uint32_t koff[4], voff[4];
    {
      const uint32_t krow = (uint32_t)(warp * 16 + li + 8 * (lj & 1)) * 256;
      const uint32_t kx = (uint32_t)((lj >> 1) ^ li);
      const uint32_t vrow = 16384u + (uint32_t)(warp * 16 + li + 8 * (lj >> 1)) * 256;
      const uint32_t vx = (uint32_t)((lj & 1) ^ li);
#pragma unroll
      for (int j = 0; j < 4; ++j) {
        koff[j] = krow + (((uint32_t)(2 * j) ^ kx) << 4);
        voff[j] = vrow + (((uint32_t)(2 * j) ^ vx) << 4);
      }
    }
    const bool diag = (t == (g >> 1));
    const bool odd = g & 1;
    uint32_t qf[16];
    float acc[8][4];
    float m_run = 0.f, l_run = 0.f;
    int ntile = 0;
    while (true) {
      mbar_wait(full0 + 32 * cs.slot + 8 * (warp >> 1), cs.par);
      const uint32_t m = meta[cs.slot];
      const uint32_t st = sb + cs.slot * kStage;
      if (m & (1u << 26)) {
        __syncwarp();
        if (lane == 0) mbar_arrive(empty0 + 8 * cs.slot);
        cs.next();
        break;
      }
      if (m & (1u << 24)) {
        const uint32_t p = m & 63;
        const uint32_t qa = sb + SM_QALL + ((p >> 5) * (kH * kDH) + (p & 31) * kDH) * 2 + t * 4;
#pragma unroll
        for (int s = 0; s < 16; ++s) qf[s] = lds32(qa + (((uint32_t)s ^ (uint32_t)g) << 4));
#pragma unroll
        for (int mt = 0; mt < 8; ++mt) acc[mt][0] = acc[mt][1] = acc[mt][2] = acc[mt][3] = 0.f;
        m_run = -INFINITY; l_run = 0.f;
      }
      float s0[4] = {0.f, 0.f, 0.f, 0.f}, s1[4] = {0.f, 0.f, 0.f, 0.f};
      {
        uint32_t a[8][4];
#pragma unroll
        for (int s = 0; s < 8; ++s) ldsm4(a[s], st + koff[s & 3] + (s >> 2) * 128);
#pragma unroll
        for (int s = 0; s < 8; s += 2) {
          mma16816(s0, a[s], qf[2 * s], qf[2 * s + 1]);
          mma16816(s1, a[s + 1], qf[2 * s + 2], qf[2 * s + 3]);
        }
      }
      mbar_wait(full0 + 32 * cs.slot + 16 + 8 * (warp >> 1), cs.par);
      uint32_t va[8][4];
#pragma unroll
      for (int mt = 0; mt < 8; ++mt) ldsm4t(va[mt], st + voff[mt & 3] + (mt >> 2) * 128);
      float x0 = odd ? (s0[1] + s1[1]) : (s0[0] + s1[0]);
      float x1 = odd ? (s0[3] + s1[3]) : (s0[2] + s1[2]);
      x0 = bf16r(bf16r(x0) * 0.08838834764831845f);
      x1 = bf16r(bf16r(x1) * 0.08838834764831845f);
      if (!diag) { x0 = -INFINITY; x1 = -INFINITY; }
      const float m_new = fmaxf(m_run, warp_max_redux(fmaxf(x0, x1)));
      const float p0 = ex2((x0 - m_new) * kLog2e), p1 = ex2((x1 - m_new) * kLog2e);
      if (m_new != m_run) {
        const float alpha = ex2((m_run - m_new) * kLog2e);
        l_run *= alpha;
#pragma unroll
        for (int mt = 0; mt < 8; ++mt) { acc[mt][0] *= alpha; acc[mt][1] *= alpha; acc[mt][2] *= alpha; acc[mt][3] *= alpha; }
        m_run = m_new;
      }
      l_run += p0 + p1;
      const uint32_t sh = odd ? 16u : 0u;
      const uint32_t b0 = (uint32_t)__bfloat16_as_ushort(__float2bfloat16_rn(p0)) << sh;
      const uint32_t b1 = (uint32_t)__bfloat16_as_ushort(__float2bfloat16_rn(p1)) << sh;
#pragma unroll
      for (int mt = 0; mt < 8; ++mt) mma16816(acc[mt], va[mt], b0, b1);
      __syncwarp();
      if (lane == 0) mbar_arrive(empty0 + 8 * cs.slot);
      cs.next();
      if (++ntile == 8) {
#pragma unroll 1
        for (int r = 0; r < 2; ++r) {
          for (int it = 0;; ++it) {
            uint4 w[8];
#pragma unroll
            for (int j = 0; j < 8; ++j) w[j] = ld_ll4(g_s.q + ((r * 8 + j) * 128 + tid) * 4);
            bool ok = true;
#pragma unroll
            for (int j = 0; j < 8; ++j) ok = ok && ok4(w[j], tag);
            if (ok) {
#pragma unroll
              for (int j = 0; j < 8; ++j)
                *reinterpret_cast<uint2*>(smem + SM_QALL + ((r * 8 + j) * 128 + tid) * 8) =
                    make_uint2(pack16(w[j].x, w[j].y), pack16(w[j].z, w[j].w));
              break;
            }
            if (it > kSpinLimit) __trap();
          }
        }
      }
      if (m & (1u << 25)) {
        float* fb = reinterpret_cast<float*>(smem + SM_FLUSH);
        float* stats = reinterpret_cast<float*>(smem + SM_STATS);
        const float lw = warp_sum(l_run);
        float* my = fb + (warp * 4 + t) * 136 + g;
#pragma unroll
        for (int mt = 0; mt < 8; ++mt) {
          const int j0 = (2 * mt) ^ (2 * t);
          my[j0 * 8] = acc[mt][0] + acc[mt][3];
          my[j0 * 8 + 8] = acc[mt][1] + acc[mt][2];
        }
        if (lane == 0) { stats[warp * 2] = m_run; stats[warp * 2 + 1] = lw; }
        cbar();
        const float m0 = stats[0], m1 = stats[2], m2 = stats[4], m3 = stats[6];
        const float mm = fmaxf(fmaxf(m0, m1), fmaxf(m2, m3));
        const float sc[4] = {ex2((m0 - mm) * kLog2e), ex2((m1 - mm) * kLog2e), ex2((m2 - mm) * kLog2e), ex2((m3 - mm) * kLog2e)};
        float o = 0.f;
#pragma unroll
        for (int w = 0; w < 4; ++w)
          o += sc[w] * ((fb[(w * 4 + 0) * 136 + tid] + fb[(w * 4 + 1) * 136 + tid]) +
                        (fb[(w * 4 + 2) * 136 + tid] + fb[(w * 4 + 3) * 136 + tid]));
        uint32_t* part = g_s.part + (size_t)((m >> 8) & 0xffff) * kPartStride;
        st_ll1(part + tid, tag32(o, tag));
        if (tid == 0) {
          const float ll = sc[0] * stats[1] + sc[1] * stats[3] + sc[2] * stats[5] + sc[3] * stats[7];
          st_ll2(part + 128, tag32(mm, tag), tag32(ll, tag));
        }
        cbar();
      }
    }
  }
  STAMP(2);
  const uint32_t* const hbox = g_s.hll + (size_t)c * kH * 16;
  const uint32_t* const obox = g_s.oll + (size_t)c * kFG * 16;
  const uint32_t* const gbox = g_s.gp + ((4 * min(h_own, kFG - 1) + 2 * ((tid & 63) >> 5)) * 4 + (tid >> 6)) * 64 + ((2 * tid) & 63);
  const uint4 hfirst = ld_ll4(hbox + tid * 4);
  const uint4 ofirst = ld_ll4(obox + min(tid, kFG * 4 - 1) * 4);
  uint2 gw[4];
  gw[0] = ld_ll2(gbox); gw[1] = ld_ll2(gbox + 128); gw[2] = ld_ll2(gbox + 256); gw[3] = ld_ll2(gbox + 384);

  {
    const int b = tid >> 6, dp = tid & 63;
    const uint32_t* pb = g_s.part + (size_t)((4 * h_own + 2 * b) * kSlots) * kPartStride;
    uint2 ml[2 * kSlots], ov[2 * kSlots];
    unsigned pending = (1u << (2 * kSlots)) - 1;
    for (int it = 0; pending; ++it) {
#pragma unroll
      for (int i = 0; i < 2 * kSlots; ++i)
        if (pending & (1u << i)) {
          ml[i] = ld_ll2(pb + i * kPartStride + 128);
          ov[i] = ld_ll2(pb + i * kPartStride + 2 * dp);
        }
#pragma unroll
      for (int i = 0; i < 2 * kSlots; ++i)
        if ((((ml[i].x ^ tag) | (ml[i].y ^ tag) | (ov[i].x ^ tag) | (ov[i].y ^ tag)) & 3u) == 0) pending &= ~(1u << i);
      if (it > kSpinLimit) __trap();
    }
    STAMP(3);
    float mm = untag32(ml[0].x);
#pragma unroll
    for (int i = 1; i < 2 * kSlots; ++i) mm = fmaxf(mm, untag32(ml[i].x));
    float ll = 0.f, o0 = 0.f, o1 = 0.f;
#pragma unroll
    for (int i = 0; i < 2 * kSlots; ++i) {
      const float sc = ex2((untag32(ml[i].x) - mm) * kLog2e);
      ll += sc * untag32(ml[i].y);
      o0 += sc * untag32(ov[i].x);
      o1 += sc * untag32(ov[i].y);
    }
    const float rl = 1.0f / ll;
    const __nv_bfloat162 pk = __floats2bfloat162_rn(o0 * rl, o1 * rl);
    *reinterpret_cast<uint32_t*>(smem + SM_OS + b * 256 + dp * 4) = *reinterpret_cast<const uint32_t*>(&pk);
  }
  cbar();
  STAMP(20);
  {
    uint32_t bfr[16];
    load_bfrag(bfr, sb + SM_OS + (g & 1) * 256 + t * 4);
    float acc[4][4] = {};
#pragma unroll
    for (int j = 0; j < 2; ++j) {
      mbar_wait(full0 + 32 * cs.slot + 8 * warp, cs.par);
      gemv_box64(acc, sb + cs.slot * kStage + warp * kUnit, bfr + 8 * j, lane);
      __syncwarp();
      if (lane == 0) mbar_arrive(empty0 + 8 * cs.slot);
      cs.next();
    }
    ll_send64<kH>(g_s.hll, 256 * r_own + 64 * warp, h_own, acc, tag, g, t);
  }
  STAMP(4);
  float hres;
  {
    const float a = ll_reduce<kH>(hbox, hfirst, tag, reinterpret_cast<float*>(smem + SM_RED2), tid);
    hres = bf16r(xres + bf16r(a));
    if (tid < 16) st_ll1(g_s.hfin + (tid & 1) * kD + 8 * c + (tid >> 1), tag16(hres, tag));
  }
  STAMP(21);
  {
    uint4 w[4];
    unsigned pending = 15;
    for (int it = 0; pending; ++it) {
#pragma unroll
      for (int k = 0; k < 4; ++k) if (pending & (1u << k)) w[k] = ld_ll4(g_s.hfin + k * 512 + lncol * 4);
#pragma unroll
      for (int k = 0; k < 4; ++k) if (ok4(w[k], tag)) pending &= ~(1u << k);
      if (it > kSpinLimit) __trap();
    }
    float v[2][8];
#pragma unroll
    for (int k = 0; k < 4; ++k) {
      v[k >> 1][4 * (k & 1) + 0] = untag16(w[k].x); v[k >> 1][4 * (k & 1) + 1] = untag16(w[k].y);
      v[k >> 1][4 * (k & 1) + 2] = untag16(w[k].z); v[k >> 1][4 * (k & 1) + 3] = untag16(w[k].w);
    }
    STAMP(5);
    layernorm2(v, smem + SM_HN, reinterpret_cast<float*>(smem + SM_LNRED), tid, lncol);
    if (c == 0 && tid == 0) { g_s.epoch = epoch + 1; g_s.tagprev = tag; }
  }
  STAMP(6);
  if (c < kFFN) {
    {
      Ring gs = cs;
      for (int j = 0; j < warp; ++j) gs.next();
      float ag[4][4] = {}, au[4][4] = {};
      const uint32_t st = sb + gs.slot * kStage, fb = full0 + 32 * gs.slot;
      uint32_t bfr[16];
      load_bfrag(bfr, sb + SM_HN + (g & 1) * (kD * 2) + (512 * (c & 1) + 128 * warp) * 2 + t * 4);
      mbar_wait(fb, gs.par);
      gemv_box64(ag, st, bfr, lane);
      mbar_wait(fb + 8, gs.par);
      gemv_box64(ag, st + kUnit, bfr + 8, lane);
      mbar_wait(fb + 16, gs.par);
      gemv_box64(au, st + 2 * kUnit, bfr, lane);
      mbar_wait(fb + 24, gs.par);
      STAMP(23);
      gemv_box64(au, st + 3 * kUnit, bfr + 8, lane);
      float* rb = reinterpret_cast<float*>(smem + SM_RBUF) + warp * 256;
      store_acc64(rb, ag, g, t);
      store_acc64(rb + 128, au, g, t);
      cs.next(); cs.next(); cs.next(); cs.next();
    }
    cbar();
    {
      const float* rb = reinterpret_cast<const float*>(smem + SM_RBUF) + (tid & 63) * 2 + (tid >> 6);
      const float sg = (rb[0] + rb[256]) + (rb[512] + rb[768]);
      const float su = (rb[128] + rb[384]) + (rb[640] + rb[896]);
      uint32_t* dst = g_s.gp + (c * 4 + (tid >> 6)) * 64 + (tid & 63);
      st_ll1(dst, tag32(sg, tag));
      st_ll1(dst + 128, tag32(su, tag));
    }
    STAMP(7);
    {
      const int b = tid >> 6, dp = tid & 63;
      for (int it = 0;; ++it) {
        const uint32_t bad = (gw[0].x ^ tag) | (gw[0].y ^ tag) | (gw[1].x ^ tag) | (gw[1].y ^ tag) |
                             (gw[2].x ^ tag) | (gw[2].y ^ tag) | (gw[3].x ^ tag) | (gw[3].y ^ tag);
        if ((bad & 3u) == 0) break;
        gw[0] = ld_ll2(gbox); gw[1] = ld_ll2(gbox + 128); gw[2] = ld_ll2(gbox + 256); gw[3] = ld_ll2(gbox + 384);
        if (it > kSpinLimit) __trap();
      }
      float a[2];
#pragma unroll
      for (int e = 0; e < 2; ++e) {
        const float gt = bf16r(untag32(e ? gw[0].y : gw[0].x) + untag32(e ? gw[2].y : gw[2].x));
        const float up = bf16r(untag32(e ? gw[1].y : gw[1].x) + untag32(e ? gw[3].y : gw[3].x));
        const float inner = 0.7978845608028654f * (gt + 0.044715f * gt * gt * gt);
        const float ge = bf16r(gt * rcp(1.0f + ex2(-2.0f * kLog2e * inner)));
        a[e] = ge * up;
      }
      const __nv_bfloat162 pk = __floats2bfloat162_rn(a[0], a[1]);
      *reinterpret_cast<uint32_t*>(smem + SM_ACT + b * 256 + dp * 4) = *reinterpret_cast<const uint32_t*>(&pk);
    }
    cbar();
    STAMP(27);
    uint32_t bfr[16];
    load_bfrag(bfr, sb + SM_ACT + (g & 1) * 256 + t * 4);
    float acc[4][4] = {};
#pragma unroll
    for (int j = 0; j < 2; ++j) {
      mbar_wait(full0 + 32 * cs.slot + 8 * warp, cs.par);
      if (j == 0) STAMP(24); else STAMP(25);
      gemv_box64(acc, sb + cs.slot * kStage + warp * kUnit, bfr + 8 * j, lane);
      cs.next();
    }
    ll_send64<kFG>(g_s.oll, 256 * r_own + 64 * warp, h_own, acc, tag, g, t);
  }
  STAMP(8);
  {
    const float d = ll_reduce<kFG>(obox, ofirst, tag, reinterpret_cast<float*>(smem + SM_RED2) + 64, tid);
    if (tid < 16) out[(tid & 1) * kD + 8 * c + (tid >> 1)] = __float2bfloat16_rn(hres + bf16r(d));
  }
  STAMP(9);
}

typedef CUresult (*EncodeTiledFn)(CUtensorMap*, CUtensorMapDataType, cuuint32_t, void*, const cuuint64_t*,
                                  const cuuint64_t*, const cuuint32_t*, const cuuint32_t*, CUtensorMapInterleave,
                                  CUtensorMapSwizzle, CUtensorMapL2promotion, CUtensorMapFloatOOBfill);

void make_map(EncodeTiledFn enc, CUtensorMap* m, const void* base, uint64_t cols, uint64_t rows, uint32_t box_cols,
              uint32_t box_rows, CUtensorMapSwizzle sw, CUtensorMapL2promotion promo) {
  cuuint64_t dims[2] = {cols, rows};
  cuuint64_t strides[1] = {cols * 2};
  cuuint32_t box[2] = {box_cols, box_rows};
  cuuint32_t es[2] = {1, 1};
  enc(m, CU_TENSOR_MAP_DATA_TYPE_BFLOAT16, 2, const_cast<void*>(base), dims, strides, box, es,
      CU_TENSOR_MAP_INTERLEAVE_NONE, sw, promo, CU_TENSOR_MAP_FLOAT_OOB_FILL_NONE);
}

}

extern "C" void kernel_launch(void* const* d_in, const int* in_sizes, int n_in, void* d_out, int out_size) {
  (void)in_sizes; (void)n_in; (void)out_size;
  static EncodeTiledFn enc = nullptr;
  if (!enc) {
    void* fn = nullptr;
    cudaDriverEntryPointQueryResult qr;
    cudaGetDriverEntryPoint("cuTensorMapEncodeTiled", &fn, cudaEnableDefault, &qr);
    enc = reinterpret_cast<EncodeTiledFn>(fn);
    cudaFuncSetAttribute(fused_decode_kernel, cudaFuncAttributeMaxDynamicSharedMemorySize, kSmemBytes);
  }
  const __nv_bfloat16* x = static_cast<const __nv_bfloat16*>(d_in[0]);
  const __nv_bfloat16* kc = static_cast<const __nv_bfloat16*>(d_in[1]);
  const __nv_bfloat16* vc = static_cast<const __nv_bfloat16*>(d_in[2]);
  CUtensorMap mq, mo, mg, mu, md;
  make_map(enc, &mq, d_in[3], kH * kDH, kD, 64, 64, CU_TENSOR_MAP_SWIZZLE_128B, CU_TENSOR_MAP_L2_PROMOTION_L2_256B);
  make_map(enc, &mo, d_in[4], kD, kH * kDH, 64, 64, CU_TENSOR_MAP_SWIZZLE_128B, CU_TENSOR_MAP_L2_PROMOTION_L2_256B);
  make_map(enc, &mg, d_in[6], kF, kD, 64, 64, CU_TENSOR_MAP_SWIZZLE_128B, CU_TENSOR_MAP_L2_PROMOTION_L2_256B);
  make_map(enc, &mu, d_in[7], kF, kD, 64, 64, CU_TENSOR_MAP_SWIZZLE_128B, CU_TENSOR_MAP_L2_PROMOTION_L2_256B);
  make_map(enc, &md, d_in[8], kD, kF, 64, 64, CU_TENSOR_MAP_SWIZZLE_128B, CU_TENSOR_MAP_L2_PROMOTION_L2_256B);
  fused_decode_kernel<<<kG, kThreads, kSmemBytes, cudaStreamPerThread>>>(mq, mo, mg, mu, md, x, kc, vc,
                                                                        static_cast<__nv_bfloat16*>(d_out));
}
```

```cpp
#include <cuda_runtime.h>
#include <cuda_bf16.h>
#include <cuda.h>
#include <stdint.h>

namespace {

constexpr int kD = 1024, kH = 32, kSK = 16384, kDH = 128, kF = 3584;
constexpr int kG = 128;
constexpr int kFB = kF / 64;
constexpr int kFFN = 2 * kFB;
constexpr int kNST = 6;
constexpr int kStage = 32768;
constexpr int kUnit = 8192;
constexpr int kTileKeys = 64;
constexpr int kHalfTiles = 128;
constexpr int kStaticTiles = 112;
constexpr int kDynHalf = 2 * (kHalfTiles - kStaticTiles);
constexpr int kLevels = 6;
constexpr int kTickets = kLevels * kG;
constexpr int kSlots = kLevels + 1;
constexpr int kPartStride = 136;
constexpr int kCapWQ = 6;
constexpr int kCapST = 8;
constexpr int kCapKV = 6;
constexpr int kCapWO = 7, kCapGU = 6, kCapDN = 5;
constexpr int kCapHi = 12;
constexpr int kThreads = 160;
constexpr float kLog2e = 1.4426950408889634f;
constexpr int kSpinLimit = 1 << 22;

constexpr int SM_QALL = kNST * kStage;
constexpr int SM_HN = SM_QALL;
constexpr int SM_RBUF = SM_QALL + 8192;
constexpr int SM_OS = SM_QALL + 12288;
constexpr int SM_ACT = SM_QALL + 12800;
constexpr int SM_XB = SM_QALL + 13312;
constexpr int SM_FLUSH = SM_QALL + 16384;
constexpr int SM_XN = SM_FLUSH;
constexpr int SM_RBUF0 = SM_FLUSH + 4096;
constexpr int SM_STATS = SM_FLUSH + 16 * 136 * 4;
constexpr int SM_LNRED = SM_STATS + 64;
constexpr int SM_RED2 = SM_LNRED + 64;
constexpr int SM_BARS = SM_RED2 + 512;
constexpr int SM_META = SM_BARS + 5 * kNST * 8 + 8;
constexpr int SM_TOTAL = SM_META + 64;
constexpr int kSmemBytes = SM_TOTAL + 1024;

static_assert(kG * kFB * 16 <= kG * kSlots * kPartStride, "FFN mailbox must fit in the partial buffer");
struct __align__(128) Scratch {
  unsigned tagprev;        unsigned pad0[31];
  unsigned ticket;         unsigned pad1[31];
  unsigned hcnt;           unsigned pad2[31];
  uint32_t qp[2 * 2 * kH * kDH];
  uint32_t q[2 * kH * kDH];
  uint32_t hfin[2 * kD];
  uint32_t part[kG * kSlots * kPartStride];
  uint32_t hll[16 * kH * 128];
};
__device__ Scratch g_s;

__device__ __forceinline__ uint32_t smem_u32(const void* p) { return (uint32_t)__cvta_generic_to_shared(p); }
__device__ __forceinline__ void mbar_init(uint32_t bar, uint32_t cnt) {
  asm volatile("mbarrier.init.shared::cta.b64 [%0], %1;" ::"r"(bar), "r"(cnt) : "memory");
}
__device__ __forceinline__ void mbar_expect_tx(uint32_t bar, uint32_t bytes) {
  asm volatile("mbarrier.arrive.expect_tx.shared::cta.b64 _, [%0], %1;" ::"r"(bar), "r"(bytes) : "memory");
}
__device__ __forceinline__ void mbar_arrive(uint32_t bar) {
  asm volatile("mbarrier.arrive.shared::cta.b64 _, [%0];" ::"r"(bar) : "memory");
}
__device__ __forceinline__ bool mbar_try(uint32_t bar, uint32_t parity) {
  uint32_t ok;
  asm volatile("{\n.reg .pred p;\nmbarrier.try_wait.parity.shared::cta.b64 p, [%1], %2;\nselp.u32 %0, 1, 0, p;\n}"
               : "=r"(ok) : "r"(bar), "r"(parity) : "memory");
  return ok;
}
__device__ __forceinline__ bool mbar_test(uint32_t bar, uint32_t parity) {
  uint32_t ok;
  asm volatile("{\n.reg .pred p;\nmbarrier.test_wait.parity.shared::cta.b64 p, [%1], %2;\nselp.u32 %0, 1, 0, p;\n}"
               : "=r"(ok) : "r"(bar), "r"(parity) : "memory");
  return ok;
}
__device__ __forceinline__ void mbar_wait_cluster(uint32_t bar, uint32_t parity) {
#pragma unroll 1
  for (int it = 0; it < (1 << 22); ++it) {
    uint32_t ok;
    asm volatile("{\n.reg .pred p;\nmbarrier.try_wait.parity.acquire.cluster.shared::cta.b64 p, [%1], %2;\nselp.u32 %0, 1, 0, p;\n}"
                 : "=r"(ok) : "r"(bar), "r"(parity) : "memory");
    if (ok) return;
  }
  __trap();
}
__device__ __forceinline__ void mbar_wait(uint32_t bar, uint32_t parity) {
  if (mbar_try(bar, parity)) return;
#pragma unroll 1
  for (int it = 0; it < (1 << 22); ++it)
    if (mbar_try(bar, parity)) return;
  __trap();
}
__device__ __forceinline__ void bulk_load(uint32_t dst, const void* src, uint32_t bytes, uint32_t bar, uint64_t pol) {
  asm volatile("cp.async.bulk.shared::cluster.global.mbarrier::complete_tx::bytes.L2::cache_hint [%0], [%1], %2, [%3], %4;"
               ::"r"(dst), "l"(src), "r"(bytes), "r"(bar), "l"(pol) : "memory");
}
__device__ __forceinline__ void tma2d(uint32_t dst, const CUtensorMap* map, int c0, int c1, uint32_t bar, uint64_t pol) {
  asm volatile("cp.async.bulk.tensor.2d.shared::cluster.global.mbarrier::complete_tx::bytes.L2::cache_hint [%0], [%1, {%3, %4}], [%2], %5;"
               ::"r"(dst), "l"(map), "r"(bar), "r"(c0), "r"(c1), "l"(pol) : "memory");
}
__device__ __forceinline__ uint64_t stream_policy() {
  uint64_t pol;
  asm("createpolicy.fractional.L2::evict_first.b64 %0, 1.0;" : "=l"(pol));
  return pol;
}
__device__ __forceinline__ void prefetch_map(const CUtensorMap* map) {
  asm volatile("prefetch.tensormap [%0];" ::"l"(map) : "memory");
}
__device__ __forceinline__ void cbar() { asm volatile("bar.sync 1, 128;" ::: "memory"); }
__device__ __forceinline__ uint32_t ld_ll1(const uint32_t* p) {
  uint32_t v;
  asm volatile("ld.relaxed.gpu.global.u32 %0, [%1];" : "=r"(v) : "l"(p) : "memory");
  return v;
}
__device__ __forceinline__ uint2 ld_ll2(const uint32_t* p) {
  uint2 v;
  asm volatile("ld.relaxed.gpu.global.v2.u32 {%0, %1}, [%2];" : "=r"(v.x), "=r"(v.y) : "l"(p) : "memory");
  return v;
}
__device__ __forceinline__ uint4 ld_ll4(const uint32_t* p) {
  uint4 v;
  asm volatile("ld.relaxed.gpu.global.v4.u32 {%0, %1, %2, %3}, [%4];" : "=r"(v.x), "=r"(v.y), "=r"(v.z), "=r"(v.w) : "l"(p) : "memory");
  return v;
}
__device__ __forceinline__ void st_ll1(uint32_t* p, uint32_t a) {
  asm volatile("st.relaxed.gpu.global.u32 [%0], %1;" ::"l"(p), "r"(a) : "memory");
}
__device__ __forceinline__ void st_ll2(uint32_t* p, uint32_t a, uint32_t b) {
  asm volatile("st.relaxed.gpu.global.v2.u32 [%0], {%1, %2};" ::"l"(p), "r"(a), "r"(b) : "memory");
}
__device__ __forceinline__ void red_add(unsigned* p, unsigned v) {
  asm volatile("red.relaxed.gpu.global.add.u32 [%0], %1;" ::"l"(p), "r"(v) : "memory");
}
__device__ __forceinline__ uint32_t tag32(float v, uint32_t tag) { return (__float_as_uint(v) & ~7u) | tag; }
__device__ __forceinline__ float untag32(uint32_t w) { return __uint_as_float(w & ~7u); }
__device__ __forceinline__ uint32_t tag16(float v, uint32_t tag) {
  return ((uint32_t)__bfloat16_as_ushort(__float2bfloat16_rn(v)) << 16) | tag;
}
__device__ __forceinline__ float untag16(uint32_t w) { return __uint_as_float(w & 0xffff0000u); }
__device__ __forceinline__ uint32_t pack16(uint32_t lo, uint32_t hi) { return __byte_perm(lo, hi, 0x7632); }
__device__ __forceinline__ bool ok4(const uint4& v, uint32_t tag) {
  return (((v.x ^ tag) | (v.y ^ tag) | (v.z ^ tag) | (v.w ^ tag)) & 7u) == 0;
}
__device__ __forceinline__ void ldsm4(uint32_t (&a)[4], uint32_t addr) {
  asm volatile("ldmatrix.sync.aligned.m8n8.x4.shared.b16 {%0,%1,%2,%3}, [%4];"
               : "=r"(a[0]), "=r"(a[1]), "=r"(a[2]), "=r"(a[3]) : "r"(addr) : "memory");
}
__device__ __forceinline__ void ldsm4t(uint32_t (&a)[4], uint32_t addr) {
  asm volatile("ldmatrix.sync.aligned.m8n8.x4.trans.shared.b16 {%0,%1,%2,%3}, [%4];"
               : "=r"(a[0]), "=r"(a[1]), "=r"(a[2]), "=r"(a[3]) : "r"(addr) : "memory");
}
__device__ __forceinline__ void mma16816(float (&c)[4], const uint32_t (&a)[4], uint32_t b0, uint32_t b1) {
  asm("mma.sync.aligned.m16n8k16.row.col.f32.bf16.bf16.f32 {%0,%1,%2,%3}, {%4,%5,%6,%7}, {%8,%9}, {%0,%1,%2,%3};"
               : "+f"(c[0]), "+f"(c[1]), "+f"(c[2]), "+f"(c[3])
               : "r"(a[0]), "r"(a[1]), "r"(a[2]), "r"(a[3]), "r"(b0), "r"(b1));
}
__device__ __forceinline__ float bf16r(float x) { return __bfloat162float(__float2bfloat16_rn(x)); }
__device__ __forceinline__ float ex2(float x) {
  float y;
  asm("ex2.approx.ftz.f32 %0, %1;" : "=f"(y) : "f"(x));
  return y;
}
__device__ __forceinline__ float rcp(float x) {
  float y;
  asm("rcp.approx.ftz.f32 %0, %1;" : "=f"(y) : "f"(x));
  return y;
}
__device__ __forceinline__ float warp_sum(float v) {
#pragma unroll
  for (int o = 16; o > 0; o >>= 1) v += __shfl_xor_sync(0xffffffffu, v, o);
  return v;
}
__device__ __forceinline__ float warp_max_redux(float v) {
  int k = __float_as_int(v);
  k ^= (k >> 31) & 0x7fffffff;
  k = __reduce_max_sync(0xffffffffu, k);
  k ^= (k >> 31) & 0x7fffffff;
  return __int_as_float(k);
}
__device__ __forceinline__ void sts32(uint32_t addr, uint32_t v) {
  asm volatile("st.volatile.shared.u32 [%0], %1;" ::"r"(addr), "r"(v) : "memory");
}
__device__ __forceinline__ uint32_t lds32v(uint32_t addr) {
  uint32_t v;
  asm volatile("ld.volatile.shared.u32 %0, [%1];" : "=r"(v) : "r"(addr) : "memory");
  return v;
}
__device__ __forceinline__ uint32_t lds32(uint32_t addr) {
  uint32_t v;
  asm volatile("ld.shared.u32 %0, [%1];" : "=r"(v) : "r"(addr) : "memory");
  return v;
}

__device__ __forceinline__ void layernorm2(const float (&v)[2][8], uint8_t* dst, float* red, int tid, int col) {
  const int lane = tid & 31, warp = tid >> 5;
  float mu[2], m2[2];
#pragma unroll
  for (int b = 0; b < 2; ++b) {
    mu[b] = (((v[b][0] + v[b][1]) + (v[b][2] + v[b][3])) + ((v[b][4] + v[b][5]) + (v[b][6] + v[b][7]))) * 0.125f;
    float q0 = 0.f, q1 = 0.f;
#pragma unroll
    for (int i = 0; i < 4; ++i) {
      const float d0 = v[b][i] - mu[b], d1 = v[b][4 + i] - mu[b];
      q0 = fmaf(d0, d0, q0); q1 = fmaf(d1, d1, q1);
    }
    m2[b] = q0 + q1;
  }
  float wgt = 4.0f;
#pragma unroll
  for (int o = 1; o < 32; o <<= 1) {
#pragma unroll
    for (int b = 0; b < 2; ++b) {
      const float mo = __shfl_xor_sync(0xffffffffu, mu[b], o), qo = __shfl_xor_sync(0xffffffffu, m2[b], o);
      const float d = mo - mu[b];
      m2[b] = fmaf(d * d, wgt, m2[b] + qo);
      mu[b] = 0.5f * (mu[b] + mo);
    }
    wgt *= 2.0f;
  }
  if (lane == 0) *reinterpret_cast<float4*>(red + warp * 4) = make_float4(mu[0], m2[0], mu[1], m2[1]);
  cbar();
  const float4 r0 = *reinterpret_cast<const float4*>(red), r1 = *reinterpret_cast<const float4*>(red + 4);
  const float4 r2 = *reinterpret_cast<const float4*>(red + 8), r3 = *reinterpret_cast<const float4*>(red + 12);
  float mb[2], rden[2];
  {
    const float a0 = 0.5f * (r0.x + r1.x), a1 = 0.5f * (r2.x + r3.x), d0 = r1.x - r0.x, d1 = r3.x - r2.x, d2 = a1 - a0;
    const float q = (r0.y + r1.y + 128.f * d0 * d0) + (r2.y + r3.y + 128.f * d1 * d1) + 256.f * d2 * d2;
    mb[0] = bf16r(0.5f * (a0 + a1));
    rden[0] = 1.0f / bf16r(sqrtf(bf16r(bf16r(q * (1.0f / kD)) + 1e-5f)));
  }
  {
    const float a0 = 0.5f * (r0.z + r1.z), a1 = 0.5f * (r2.z + r3.z), d0 = r1.z - r0.z, d1 = r3.z - r2.z, d2 = a1 - a0;
    const float q = (r0.w + r1.w + 128.f * d0 * d0) + (r2.w + r3.w + 128.f * d1 * d1) + 256.f * d2 * d2;
    mb[1] = bf16r(0.5f * (a0 + a1));
    rden[1] = 1.0f / bf16r(sqrtf(bf16r(bf16r(q * (1.0f / kD)) + 1e-5f)));
  }
#pragma unroll
  for (int b = 0; b < 2; ++b) {
#pragma unroll
    for (int k = 0; k < 2; ++k) {
      const __nv_bfloat162 dl = __floats2bfloat162_rn(v[b][4 * k] - mb[b], v[b][4 * k + 1] - mb[b]);
      const __nv_bfloat162 dh = __floats2bfloat162_rn(v[b][4 * k + 2] - mb[b], v[b][4 * k + 3] - mb[b]);
      const __nv_bfloat162 lo = __floats2bfloat162_rn(__low2float(dl) * rden[b], __high2float(dl) * rden[b]);
      const __nv_bfloat162 hi = __floats2bfloat162_rn(__low2float(dh) * rden[b], __high2float(dh) * rden[b]);
      *reinterpret_cast<uint2*>(dst + b * (kD * 2) + k * 1024 + col * 8) =
          make_uint2(*reinterpret_cast<const uint32_t*>(&lo), *reinterpret_cast<const uint32_t*>(&hi));
    }
  }
  cbar();
}

__device__ __forceinline__ void gemv_box64(float (&acc)[4][4], uint32_t box, const uint32_t* b, int lane) {
  const int li = lane & 7, lj = lane >> 3;
  const uint32_t row = box + (li + 8 * (lj >> 1)) * 128;
  uint32_t a[4][4][4];
#pragma unroll
  for (int s = 0; s < 4; ++s) {
#pragma unroll
    for (int mt = 0; mt < 4; ++mt)
      ldsm4t(a[s][mt], row + s * 2048 + ((((uint32_t)(2 * mt + (lj & 1))) ^ (uint32_t)li) << 4));
  }
#pragma unroll
  for (int s = 0; s < 4; ++s) {
#pragma unroll
    for (int mt = 0; mt < 4; ++mt) mma16816(acc[mt], a[s][mt], b[2 * s], b[2 * s + 1]);
  }
}

__device__ __forceinline__ void load_box64(uint32_t (&a)[4][4][4], uint32_t box, int lane) {
  const int li = lane & 7, lj = lane >> 3;
  const uint32_t row = box + (li + 8 * (lj >> 1)) * 128;
#pragma unroll
  for (int s = 0; s < 4; ++s) {
#pragma unroll
    for (int mt = 0; mt < 4; ++mt)
      ldsm4t(a[s][mt], row + s * 2048 + ((((uint32_t)(2 * mt + (lj & 1))) ^ (uint32_t)li) << 4));
  }
}
__device__ __forceinline__ void mma_box64(float (&acc)[4][4], const uint32_t (&a)[4][4][4], const uint32_t* b) {
#pragma unroll
  for (int s = 0; s < 4; ++s) {
#pragma unroll
    for (int mt = 0; mt < 4; ++mt) mma16816(acc[mt], a[s][mt], b[2 * s], b[2 * s + 1]);
  }
}

__device__ __forceinline__ void load_bfrag(uint32_t (&b)[16], uint32_t addr) {
#pragma unroll
  for (int s = 0; s < 16; ++s) b[s] = lds32(addr + s * 16);
}

__device__ __forceinline__ void store_acc64(float* dst, const float (&acc)[4][4], int g, int t) {
  if (t < 2) {
#pragma unroll
    for (int mt = 0; mt < 4; ++mt)
      *reinterpret_cast<float2*>(dst + (16 * mt + 8 * t + g) * 2) =
          t == 0 ? make_float2(acc[mt][0], acc[mt][1]) : make_float2(acc[mt][2], acc[mt][3]);
  }
}

template <int NSRC>
__device__ __forceinline__ void ll_send64(uint32_t* buf, int n0, int src, const float (&acc)[4][4], uint32_t tag, int g, int t) {
  if (t < 2) {
#pragma unroll
    for (int mt = 0; mt < 4; ++mt) {
      const float v0 = t == 0 ? acc[mt][0] : acc[mt][2], v1 = t == 0 ? acc[mt][1] : acc[mt][3];
      st_ll2(buf + ((n0 / 8 + 2 * mt + t) * NSRC + src) * 16 + g * 2, tag32(v0, tag), tag32(v1, tag));
    }
  }
}

template <int NSRC>
__device__ __forceinline__ float ll_reduce(const uint32_t* buf, uint32_t tag, float* red, int tid) {
  uint4 w0 = make_uint4(0, 0, 0, 0), w1 = w0;
  const int lane = tid & 31, warp = tid >> 5;
  const bool two = NSRC > 32 && tid + 128 < NSRC * 4;
#pragma unroll 1
  for (int it = 0;; ++it) {
    const bool ok0 = ok4(w0, tag), ok1 = !two || ok4(w1, tag);
    if (__all_sync(0xffffffffu, ok0 && ok1)) break;
    if (!ok0) w0 = ld_ll4(buf + tid * 4);
    if (!ok1) w1 = ld_ll4(buf + (tid + 128) * 4);
    if (it > kSpinLimit) __trap();
  }
  float s[4] = {untag32(w0.x), untag32(w0.y), untag32(w0.z), untag32(w0.w)};
  if (two) { s[0] += untag32(w1.x); s[1] += untag32(w1.y); s[2] += untag32(w1.z); s[3] += untag32(w1.w); }
#pragma unroll
  for (int o = 4; o <= 16; o <<= 1) {
#pragma unroll
    for (int e = 0; e < 4; ++e) s[e] += __shfl_xor_sync(0xffffffffu, s[e], o);
  }
  if (lane < 4) *reinterpret_cast<float4*>(red + warp * 16 + lane * 4) = make_float4(s[0], s[1], s[2], s[3]);
  cbar();
  float r = 0.f;
  if (tid < 16) r = (red[tid] + red[16 + tid]) + (red[32 + tid] + red[48 + tid]);
  return r;
}

struct Ring {
  int slot; uint32_t par;
  __device__ __forceinline__ void next() { if (++slot == kNST) { slot = 0; par ^= 1; } }
};

__global__ void __cluster_dims__(2, 1, 1) __launch_bounds__(kThreads, 1)
fused_decode_kernel(const __grid_constant__ CUtensorMap map_wq, const __grid_constant__ CUtensorMap map_wo,
                    const __grid_constant__ CUtensorMap map_wg, const __grid_constant__ CUtensorMap map_wu,
                    const __grid_constant__ CUtensorMap map_wd,
                    const __nv_bfloat16* __restrict__ x, const __nv_bfloat16* __restrict__ kc,
                    const __nv_bfloat16* __restrict__ vc, __nv_bfloat16* __restrict__ out) {
  extern __shared__ uint8_t smem_raw[];
  uint8_t* smem = smem_raw + ((1024u - (smem_u32(smem_raw) & 1023u)) & 1023u);
  const uint32_t sb = smem_u32(smem);
  const int tid = threadIdx.x, lane = tid & 31, warp = tid >> 5;
  const int c = blockIdx.x;
  const uint32_t full0 = sb + SM_BARS, empty0 = sb + SM_BARS + 4 * kNST * 8;
  const uint32_t xbar = empty0 + kNST * 8;
  const uint32_t meta = sb + SM_META;

  if (tid == 128) {
    prefetch_map(&map_wq);
    sts32(meta + 32, 0);
#pragma unroll
    for (int s = 0; s < kNST; ++s) {
      mbar_init(empty0 + 8 * s, 4);
#pragma unroll
      for (int j = 0; j < 4; ++j) mbar_init(full0 + 32 * s + 8 * j, 1);
    }
    mbar_init(xbar, 1);
    mbar_expect_tx(xbar, 1024);
    asm volatile("fence.mbarrier_init.release.cluster;" ::: "memory");
    asm volatile("fence.proxy.async.shared::cta;" ::: "memory");
#pragma unroll
    for (int j = 0; j < kCapWQ; ++j) {
      mbar_expect_tx(full0 + 8 * j, kUnit);
      tma2d(sb + j * kUnit, &map_wq, 64 * (c >> 1), 512 * (c & 1) + 64 * j, full0 + 8 * j, stream_policy());
    }
  }
  const int lncol = (tid + 8 * c) & 127;
  __syncthreads();
  asm volatile("barrier.cluster.arrive.relaxed.aligned;" ::: "memory");

  if (warp == 4) {
    if (lane == 0) {
      const uint64_t pol = stream_policy();
      static_assert(kCapWQ > 4 && kCapWQ < 8, "prologue issues the first wq units");
      int slot = 1;
      int i = 1;
      Ring wt{0, 0};
      int waited = 0;
      int lpos = 0; uint32_t lpar = 0;
      int inflight = kCapWQ;
      uint32_t dmask = (1u << kCapWQ) - 1;
      auto begin_stage = [&]() {
#pragma unroll 1
        while (waited < i - kNST + 1) { mbar_wait(empty0 + 8 * wt.slot, wt.par); wt.next(); ++waited; }
      };
      auto begin_unit = [&](int j, int cap) -> uint32_t {
#pragma unroll 1
        while (inflight >= cap) {
          mbar_wait(full0 + 8 * lpos, lpar);
          inflight -= (dmask >> lpos) & 1;
          if (++lpos == 4 * kNST) { lpos = 0; lpar ^= 1; }
        }
        ++inflight;
        dmask |= 1u << (4 * slot + j);
        const uint32_t bar = full0 + 32 * slot + 8 * j;
        mbar_expect_tx(bar, kUnit);
        return bar;
      };
      auto begin_unit_boost = [&](int j, int cap_lo) -> uint32_t {
#pragma unroll 1
        for (int it = 0; inflight >= (lds32v(meta + 32) ? kCapHi : cap_lo); ++it) {
          if (mbar_test(full0 + 8 * lpos, lpar)) {
            inflight -= (dmask >> lpos) & 1;
            if (++lpos == 4 * kNST) { lpos = 0; lpar ^= 1; }
          }
          if (it > (1 << 26)) __trap();
        }
        ++inflight;
        dmask |= 1u << (4 * slot + j);
        const uint32_t bar = full0 + 32 * slot + 8 * j;
        mbar_expect_tx(bar, kUnit);
        return bar;
      };
      auto empty_unit = [&](int j) {
        dmask &= ~(1u << (4 * slot + j));
        mbar_arrive(full0 + 32 * slot + 8 * j);
      };
      auto end_stage = [&]() { ++i; if (++slot == kNST) slot = 0; };
#pragma unroll 1
      for (int j = kCapWQ; j < 8; ++j) {
        const uint32_t bar = begin_unit(j & 3, kCapWQ);
        tma2d(sb + slot * kStage + (j & 3) * kUnit, &map_wq, 64 * (c >> 1), 512 * (c & 1) + 64 * j, bar, pol);
        if ((j & 3) == 3) end_stage();
      }
      int hp = c, start = 0, len = 2 * kStaticTiles, level = 0;
      unsigned nxt = 0;
      while (true) {
        const int h = hp >> 2, b = (hp >> 1) & 1, half = hp & 1;
        const size_t base = ((size_t)(b * kH + h) * kSK + (size_t)(half * kHalfTiles * kTileKeys + start * 32)) * kDH;
        const char* ksrc = reinterpret_cast<const char*>(kc + base);
        const char* vsrc = reinterpret_cast<const char*>(vc + base);
        const int cap = level == 0 ? kCapST : kCapKV;
        const uint32_t mbase = (uint32_t)(b * kH + h) | ((uint32_t)(hp * kSlots + level) << 8);
        if (len == 1) {
          nxt = atomicAdd(&g_s.ticket, 1u);
          begin_stage();
          sts32(meta + 4 * slot, mbase | (1u << 24) | (1u << 25) | (1u << 27));
          const uint32_t dst = sb + slot * kStage;
          uint32_t bar;
          bar = begin_unit(0, kCapKV); bulk_load(dst, ksrc, kUnit, bar, pol);
          empty_unit(1);
          bar = begin_unit(2, kCapKV); bulk_load(dst + 2 * kUnit, vsrc, kUnit, bar, pol);
          empty_unit(3);
          end_stage();
        } else {
          const int nst = len >> 1;
#pragma unroll 1
          for (int tt = 0; tt < nst; ++tt) {
            begin_stage();
            const uint32_t dst = sb + slot * kStage;
            sts32(meta + 4 * slot, mbase | (tt == 0 ? 1u << 24 : 0u) | (tt == nst - 1 ? 1u << 25 : 0u));
            uint32_t bar;
            bar = begin_unit(0, cap); bulk_load(dst, ksrc, kUnit, bar, pol);
            bar = begin_unit(1, cap); bulk_load(dst + kUnit, ksrc + kUnit, kUnit, bar, pol);
            if (tt == nst - 1) nxt = atomicAdd(&g_s.ticket, 1u);
            bar = begin_unit(2, cap); bulk_load(dst + 2 * kUnit, vsrc, kUnit, bar, pol);
            bar = begin_unit(3, cap); bulk_load(dst + 3 * kUnit, vsrc + kUnit, kUnit, bar, pol);
            ksrc += 2 * kUnit; vsrc += 2 * kUnit;
            end_stage();
          }
        }
        if (level == 0) { prefetch_map(&map_wo); prefetch_map(&map_wg); prefetch_map(&map_wu); prefetch_map(&map_wd); }
        if (nxt >= (unsigned)kTickets) break;
        const int lv = (int)(nxt >> 7);
        hp = (int)(nxt & 127);
        level = lv + 1;
        len = lv >= kLevels - 2 ? 1 : ((kDynHalf / 2) >> lv);
        start = 2 * kStaticTiles + (lv == kLevels - 1 ? kDynHalf - 1 : kDynHalf - (kDynHalf >> lv));
      }
      begin_stage();
      sts32(meta + 4 * slot, 1u << 26);
#pragma unroll 1
      for (int j = 0; j < 4; ++j) empty_unit(j);
      end_stage();
#pragma unroll 1
      for (int j = 0; j < 8; ++j) {
        if ((j & 3) == 0) begin_stage();
        const uint32_t bar = begin_unit(j & 3, kCapWO);
        tma2d(sb + slot * kStage + (j & 3) * kUnit, &map_wo, 256 * (c & 3) + 64 * (j & 3), 128 * (c >> 2) + 64 * (j >> 2), bar, pol);
        if ((j & 3) == 3) end_stage();
      }
      if (c < kFFN) {
#pragma unroll 1
        for (int j = 0; j < 16; ++j) {
          if ((j & 3) == 0) begin_stage();
          const uint32_t bar = begin_unit_boost(j & 3, kCapGU);
          tma2d(sb + slot * kStage + (j & 3) * kUnit, (j & 8) ? &map_wu : &map_wg, 64 * (c >> 1),
                512 * (c & 1) + 64 * (j & 7), bar, pol);
          if ((j & 3) == 3) end_stage();
        }
#pragma unroll 1
        for (int j = 0; j < 8; ++j) {
          if ((j & 3) == 0) begin_stage();
          const uint32_t bar = begin_unit_boost(j & 3, kCapDN);
          tma2d(sb + slot * kStage + (j & 3) * kUnit, &map_wd, 512 * (c & 1) + 64 * j, 64 * (c >> 1), bar, pol);
          if ((j & 3) == 3) end_stage();
        }
      }
    }
    return;
  }

  const uint32_t tagprev = ld_ll1(&g_s.tagprev);
  const int g = lane >> 2, t = lane & 3;
  const int li = lane & 7, lj = lane >> 3;
  const int h_own = c >> 2, r_own = c & 3;

  float xres = 0.f;
  if (c >= kFFN) xres = __bfloat162float(x[(tid & 1) * kD + 64 * (c - kFFN) + (tid >> 1)]);
  {
    float v[2][8];
#pragma unroll
    for (int b = 0; b < 2; ++b) {
#pragma unroll
      for (int k = 0; k < 2; ++k) {
        const uint2 pk = *reinterpret_cast<const uint2*>(x + b * kD + k * 512 + lncol * 4);
        v[b][4 * k] = __uint_as_float(pk.x << 16);     v[b][4 * k + 1] = __uint_as_float(pk.x & 0xffff0000u);
        v[b][4 * k + 2] = __uint_as_float(pk.y << 16); v[b][4 * k + 3] = __uint_as_float(pk.y & 0xffff0000u);
      }
    }
    layernorm2(v, smem + SM_XN, reinterpret_cast<float*>(smem + SM_LNRED), tid, lncol);
  }
  const uint32_t tag = tagprev % 3u + 1u;
  Ring cs{0, 0};
  {
    float acc[4][4] = {};
    uint32_t bfr[16];
    load_bfrag(bfr, sb + SM_XN + (g & 1) * (kD * 2) + (512 * (c & 1) + 128 * warp) * 2 + t * 4);
    mbar_wait(full0 + 16 * warp, 0);
    gemv_box64(acc, sb + warp * 16384, bfr, lane);
    mbar_wait(full0 + 16 * warp + 8, 0);
    gemv_box64(acc, sb + warp * 16384 + kUnit, bfr + 8, lane);
    __syncwarp();
    if (lane == 0) { mbar_arrive(empty0); mbar_arrive(empty0 + 8); }
    store_acc64(reinterpret_cast<float*>(smem + SM_RBUF0) + warp * 128, acc, g, t);
    cbar();
    {
      const float* r0 = reinterpret_cast<const float*>(smem + SM_RBUF0) + (tid & 63) * 2 + (tid >> 6);
      const float s = (r0[0] + r0[128]) + (r0[256] + r0[384]);
      st_ll1(g_s.qp + ((c & 1) * 2 + (tid >> 6)) * (kH * kDH) + 64 * (c >> 1) + (tid & 63), tag32(s, tag));
    }
    if (warp == 0) {
      const int qo = ((c >> 1) & 1) * (kH * kDH) + h_own * kDH + 4 * lane;
      uint4 w0, w1;
#pragma unroll 1
      for (int it = 0;; ++it) {
        w0 = ld_ll4(g_s.qp + qo); w1 = ld_ll4(g_s.qp + 2 * kH * kDH + qo);
        if (__all_sync(0xffffffffu, ok4(w0, tag) && ok4(w1, tag))) break;
        if (it > kSpinLimit) __trap();
      }
      const uint32_t q0 = tag16(untag32(w0.x) + untag32(w1.x), tag), q1 = tag16(untag32(w0.y) + untag32(w1.y), tag);
      const uint32_t q2 = tag16(untag32(w0.z) + untag32(w1.z), tag), q3 = tag16(untag32(w0.w) + untag32(w1.w), tag);
      *reinterpret_cast<uint2*>(smem + SM_QALL + qo * 2) = make_uint2(pack16(q0, q1), pack16(q2, q3));
      if ((c & 1) == 0) { st_ll2(g_s.q + qo, q0, q1); st_ll2(g_s.q + qo + 2, q2, q3); }
    }
    cbar();
    cs.next(); cs.next();
  }
  asm volatile("barrier.cluster.wait.acquire.aligned;" ::: "memory");

  {
    uint32_t koff[4], voff[4];
    {
      const uint32_t krow = (uint32_t)(warp * 16 + li + 8 * (lj & 1)) * 256;
      const uint32_t kx = (uint32_t)((lj >> 1) ^ li);
      const uint32_t vrow = 16384u + (uint32_t)(warp * 16 + li + 8 * (lj >> 1)) * 256;
      const uint32_t vx = (uint32_t)((lj & 1) ^ li);
#pragma unroll
      for (int j = 0; j < 4; ++j) {
        koff[j] = krow + (((uint32_t)(2 * j) ^ kx) << 4);
        voff[j] = vrow + (((uint32_t)(2 * j) ^ vx) << 4);
      }
    }
    const bool diag = (t == (g >> 1));
    const bool odd = g & 1;
    uint32_t qf[16];
    float acc[8][4];
    float m_run = 0.f, l_run = 0.f;
    int ntile = 0;
    while (true) {
      mbar_wait(full0 + 32 * cs.slot + 8 * (warp >> 1), cs.par);
      const uint32_t m = lds32v(meta + 4 * cs.slot);
      const uint32_t st = sb + cs.slot * kStage;
      if (m & (1u << 26)) {
        __syncwarp();
        if (lane == 0) mbar_arrive(empty0 + 8 * cs.slot);
        cs.next();
        break;
      }
      if (m & (1u << 24)) {
        const uint32_t p = m & 63;
        const uint32_t qa = sb + SM_QALL + ((p >> 5) * (kH * kDH) + (p & 31) * kDH) * 2 + t * 4;
#pragma unroll
        for (int s = 0; s < 16; ++s) qf[s] = lds32(qa + (((uint32_t)s ^ (uint32_t)g) << 4));
#pragma unroll
        for (int mt = 0; mt < 8; ++mt) acc[mt][0] = acc[mt][1] = acc[mt][2] = acc[mt][3] = 0.f;
        m_run = -INFINITY; l_run = 0.f;
      }
      if (!((m & (1u << 27)) && warp >= 2)) {
        float s0[4] = {0.f, 0.f, 0.f, 0.f}, s1[4] = {0.f, 0.f, 0.f, 0.f};
        {
          uint32_t a[8][4];
#pragma unroll
          for (int s = 0; s < 8; ++s) ldsm4(a[s], st + koff[s & 3] + (s >> 2) * 128);
#pragma unroll
          for (int s = 0; s < 8; s += 2) {
            mma16816(s0, a[s], qf[2 * s], qf[2 * s + 1]);
            mma16816(s1, a[s + 1], qf[2 * s + 2], qf[2 * s + 3]);
          }
        }
        mbar_wait(full0 + 32 * cs.slot + 16 + 8 * (warp >> 1), cs.par);
        uint32_t va[8][4];
#pragma unroll
        for (int mt = 0; mt < 8; ++mt) ldsm4t(va[mt], st + voff[mt & 3] + (mt >> 2) * 128);
        float x0 = odd ? (s0[1] + s1[1]) : (s0[0] + s1[0]);
        float x1 = odd ? (s0[3] + s1[3]) : (s0[2] + s1[2]);
        x0 = bf16r(bf16r(x0) * 0.08838834764831845f);
        x1 = bf16r(bf16r(x1) * 0.08838834764831845f);
        if (!diag) { x0 = -INFINITY; x1 = -INFINITY; }
        const float m_new = fmaxf(m_run, warp_max_redux(fmaxf(x0, x1)));
        const float p0 = ex2((x0 - m_new) * kLog2e), p1 = ex2((x1 - m_new) * kLog2e);
        if (m_new != m_run) {
          const float alpha = ex2((m_run - m_new) * kLog2e);
          l_run *= alpha;
#pragma unroll
          for (int mt = 0; mt < 8; ++mt) { acc[mt][0] *= alpha; acc[mt][1] *= alpha; acc[mt][2] *= alpha; acc[mt][3] *= alpha; }
          m_run = m_new;
        }
        l_run += p0 + p1;
        const uint32_t sh = odd ? 16u : 0u;
        const uint32_t b0 = (uint32_t)__bfloat16_as_ushort(__float2bfloat16_rn(p0)) << sh;
        const uint32_t b1 = (uint32_t)__bfloat16_as_ushort(__float2bfloat16_rn(p1)) << sh;
#pragma unroll
        for (int mt = 0; mt < 8; ++mt) mma16816(acc[mt], va[mt], b0, b1);
      }
      __syncwarp();
      if (lane == 0) mbar_arrive(empty0 + 8 * cs.slot);
      cs.next();
      if (++ntile == 8) {
#pragma unroll 1
        for (int r = 0; r < 2; ++r) {
          uint4 w[8];
#pragma unroll 1
          for (int it = 0;; ++it) {
#pragma unroll
            for (int j = 0; j < 8; ++j) w[j] = ld_ll4(g_s.q + ((r * 8 + j) * 128 + tid) * 4);
            bool ok = true;
#pragma unroll
            for (int j = 0; j < 8; ++j) ok = ok && ok4(w[j], tag);
            if (__all_sync(0xffffffffu, ok)) break;
            if (it > kSpinLimit) __trap();
          }
#pragma unroll
          for (int j = 0; j < 8; ++j)
            *reinterpret_cast<uint2*>(smem + SM_QALL + ((r * 8 + j) * 128 + tid) * 8) =
                make_uint2(pack16(w[j].x, w[j].y), pack16(w[j].z, w[j].w));
        }
      }
      if (m & (1u << 25)) {
        float* fb = reinterpret_cast<float*>(smem + SM_FLUSH);
        float* stats = reinterpret_cast<float*>(smem + SM_STATS);
        const float lw = warp_sum(l_run);
        float* my = fb + (warp * 4 + t) * 136 + g;
#pragma unroll
        for (int mt = 0; mt < 8; ++mt) {
          const int j0 = (2 * mt) ^ (2 * t);
          my[j0 * 8] = acc[mt][0] + acc[mt][3];
          my[j0 * 8 + 8] = acc[mt][1] + acc[mt][2];
        }
        if (lane == 0) { stats[warp * 2] = m_run; stats[warp * 2 + 1] = lw; }
        cbar();
        const float m0 = stats[0], m1 = stats[2], m2 = stats[4], m3 = stats[6];
        const float mm = fmaxf(fmaxf(m0, m1), fmaxf(m2, m3));
        const float sc[4] = {ex2((m0 - mm) * kLog2e), ex2((m1 - mm) * kLog2e), ex2((m2 - mm) * kLog2e), ex2((m3 - mm) * kLog2e)};
        float o = 0.f;
#pragma unroll
        for (int w = 0; w < 4; ++w)
          o += sc[w] * ((fb[(w * 4 + 0) * 136 + tid] + fb[(w * 4 + 1) * 136 + tid]) +
                        (fb[(w * 4 + 2) * 136 + tid] + fb[(w * 4 + 3) * 136 + tid]));
        uint32_t* part = g_s.part + (size_t)((m >> 8) & 0xffff) * kPartStride;
        st_ll1(part + tid, tag32(o, tag));
        if (tid == 0) {
          const float ll = sc[0] * stats[1] + sc[1] * stats[3] + sc[2] * stats[5] + sc[3] * stats[7];
          st_ll2(part + 128, tag32(mm, tag), tag32(ll, tag));
        } else if (tid < 4) {
          st_ll2(part + 128 + 2 * tid, tag, tag);
        }
        cbar();
      }
    }
  }
  {
    const int b = tid >> 6, dp = tid & 63;
    const uint32_t* pb = g_s.part + (size_t)((4 * h_own + 2 * b) * kSlots) * kPartStride;
    uint2 ml[2 * kSlots], ov[2 * kSlots];
    unsigned pending = (1u << (2 * kSlots)) - 1;
#pragma unroll 1
    for (int it = 0;; ++it) {
#pragma unroll
      for (int i = 0; i < 2 * kSlots; ++i)
        if (pending & (1u << i)) {
          ml[i] = ld_ll2(pb + i * kPartStride + 128);
          ov[i] = ld_ll2(pb + i * kPartStride + 2 * dp);
        }
      unsigned bad = 0;
#pragma unroll
      for (int i = 0; i < 2 * kSlots; ++i)
        if ((((ml[i].x ^ tag) | (ml[i].y ^ tag) | (ov[i].x ^ tag) | (ov[i].y ^ tag)) & 7u) != 0) bad |= 1u << i;
      pending = __reduce_or_sync(0xffffffffu, bad);
      if (!pending) break;
      if (it > kSpinLimit) __trap();
    }
    float mm = untag32(ml[0].x);
#pragma unroll
    for (int i = 1; i < 2 * kSlots; ++i) mm = fmaxf(mm, untag32(ml[i].x));
    float ll = 0.f, o0 = 0.f, o1 = 0.f;
#pragma unroll
    for (int i = 0; i < 2 * kSlots; ++i) {
      const float sc = ex2((untag32(ml[i].x) - mm) * kLog2e);
      ll += sc * untag32(ml[i].y);
      o0 += sc * untag32(ov[i].x);
      o1 += sc * untag32(ov[i].y);
    }
    const float rl = 1.0f / ll;
    const __nv_bfloat162 pk = __floats2bfloat162_rn(o0 * rl, o1 * rl);
    *reinterpret_cast<uint32_t*>(smem + SM_OS + b * 256 + dp * 4) = *reinterpret_cast<const uint32_t*>(&pk);
  }
  const uint32_t* const hbox = g_s.hll + (size_t)(c >= kFFN ? c - kFFN : 0) * kH * 128 + warp * 128 + lane * 4;
  const uint32_t* const obox = g_s.part + (size_t)c * kFB * 16;
  uint4 hw[8];
  if (c >= kFFN) {
#pragma unroll
    for (int j = 0; j < 8; ++j) hw[j] = ld_ll4(hbox + j * 512);
  }
  cbar();
  {
    uint32_t bfr[16];
    load_bfrag(bfr, sb + SM_OS + (g & 1) * 256 + t * 4);
    float acc[4][4] = {};
#pragma unroll
    for (int j = 0; j < 2; ++j) {
      mbar_wait(full0 + 32 * cs.slot + 8 * warp, cs.par);
      gemv_box64(acc, sb + cs.slot * kStage + warp * kUnit, bfr + 8 * j, lane);
      __syncwarp();
      if (lane == 0) mbar_arrive(empty0 + 8 * cs.slot);
      cs.next();
    }
    if (t < 2) {
      uint32_t* dst = g_s.hll + ((4 * r_own + warp) * kH + h_own) * 128 + (8 * t + g) * 2;
#pragma unroll
      for (int mt = 0; mt < 4; ++mt)
        st_ll2(dst + mt * 32, tag32(t == 0 ? acc[mt][0] : acc[mt][2], tag), tag32(t == 0 ? acc[mt][1] : acc[mt][3], tag));
    }
  }
  uint32_t ga0[4][4][4], ga1[4][4][4];
  if (c < kFFN) {
    Ring gs = cs;
    if (warp >= 2) gs.next();
    const uint32_t st = sb + gs.slot * kStage + (warp & 1) * 16384, fb = full0 + 32 * gs.slot + 16 * (warp & 1);
    mbar_wait(fb, gs.par);
    load_box64(ga0, st, lane);
    mbar_wait(fb + 8, gs.par);
    load_box64(ga1, st + kUnit, lane);
  }
  if (c >= kFFN) {
#pragma unroll 1
    for (int it = 0;; ++it) {
      unsigned bad = 0;
#pragma unroll
      for (int j = 0; j < 8; ++j) if (!ok4(hw[j], tag)) bad |= 1u << j;
      bad = __reduce_or_sync(0xffffffffu, bad);
      if (!bad) break;
#pragma unroll
      for (int j = 0; j < 8; ++j) if (bad & (1u << j)) hw[j] = ld_ll4(hbox + j * 512);
      if (it > kSpinLimit) __trap();
    }
    float4 s = make_float4(0.f, 0.f, 0.f, 0.f);
#pragma unroll
    for (int j = 0; j < 8; ++j) { s.x += untag32(hw[j].x); s.y += untag32(hw[j].y); s.z += untag32(hw[j].z); s.w += untag32(hw[j].w); }
    float* rb = reinterpret_cast<float*>(smem + SM_RBUF);
    *reinterpret_cast<float4*>(rb + warp * 128 + lane * 4) = s;
    cbar();
    const float a = (rb[tid] + rb[128 + tid]) + (rb[256 + tid] + rb[384 + tid]);
    st_ll1(g_s.hfin + (tid & 1) * kD + 64 * (c - kFFN) + (tid >> 1), tag16(xres + bf16r(a), tag));
    __syncwarp();
    if (lane == 0) red_add(&g_s.hcnt, 1u);
  } else {
    if (warp == 0) {
#pragma unroll 1
      for (int it = 0; ld_ll1(&g_s.hcnt) < 64u; ++it)
        if (it > kSpinLimit) __trap();
    }
    cbar();
  }
  uint32_t hown = 0;
  const uint32_t* const hown_p = g_s.hfin + (tid & 1) * kD + 8 * c + ((tid & 15) >> 1);
  if (tid < 16) hown = ld_ll1(hown_p);
  if (c < kFFN) {
    uint4 w[4];
    unsigned pending = 15;
#pragma unroll 1
    for (int it = 0;; ++it) {
#pragma unroll
      for (int k = 0; k < 4; ++k) if (pending & (1u << k)) w[k] = ld_ll4(g_s.hfin + k * 512 + lncol * 4);
      unsigned bad = 0;
#pragma unroll
      for (int k = 0; k < 4; ++k) if (!ok4(w[k], tag)) bad |= 1u << k;
      pending = __reduce_or_sync(0xffffffffu, bad);
      if (!pending) break;
      if (it > kSpinLimit) __trap();
    }
    float v[2][8];
#pragma unroll
    for (int k = 0; k < 4; ++k) {
      v[k >> 1][4 * (k & 1) + 0] = untag16(w[k].x); v[k >> 1][4 * (k & 1) + 1] = untag16(w[k].y);
      v[k >> 1][4 * (k & 1) + 2] = untag16(w[k].z); v[k >> 1][4 * (k & 1) + 3] = untag16(w[k].w);
    }
    if (lane == 0 && warp == 0) sts32(meta + 32, 1);
    layernorm2(v, smem + SM_HN, reinterpret_cast<float*>(smem + SM_LNRED), tid, lncol);
  }
  if (c < kFFN) {
    {
      Ring gs = cs;
      gs.next(); gs.next();
      if (warp >= 2) gs.next();
      float ag[4][4] = {}, au[4][4] = {};
      const uint32_t st = sb + gs.slot * kStage + (warp & 1) * 16384, fb = full0 + 32 * gs.slot + 16 * (warp & 1);
      uint32_t bfr[16];
      load_bfrag(bfr, sb + SM_HN + (g & 1) * (kD * 2) + (512 * (c & 1) + 128 * warp) * 2 + t * 4);
      mma_box64(ag, ga0, bfr);
      mma_box64(ag, ga1, bfr + 8);
      mbar_wait(fb, gs.par);
      gemv_box64(au, st, bfr, lane);
      mbar_wait(fb + 8, gs.par);
      gemv_box64(au, st + kUnit, bfr + 8, lane);
      float* rb = reinterpret_cast<float*>(smem + SM_RBUF) + warp * 256;
      store_acc64(rb, ag, g, t);
      store_acc64(rb + 128, au, g, t);
      cs.next(); cs.next(); cs.next(); cs.next();
    }
    cbar();
    {
      const int b = tid >> 6, col = tid & 63;
      const float* rb = reinterpret_cast<const float*>(smem + SM_RBUF) + col * 2 + b;
      const float sg = (rb[0] + rb[256]) + (rb[512] + rb[768]);
      const float su = (rb[128] + rb[384]) + (rb[640] + rb[896]);
      uint32_t rdst, rbar;
      asm volatile("mapa.shared::cluster.u32 %0, %1, %2;" : "=r"(rdst) : "r"(sb + SM_XB + tid * 8), "r"((c & 1) ^ 1));
      asm volatile("mapa.shared::cluster.u32 %0, %1, %2;" : "=r"(rbar) : "r"(xbar), "r"((c & 1) ^ 1));
      asm volatile("st.async.weak.shared::cluster.mbarrier::complete_tx::bytes.v2.f32 [%0], {%1, %2}, [%3];"
                   ::"r"(rdst), "f"(sg), "f"(su), "r"(rbar) : "memory");
      mbar_wait_cluster(xbar, 0);
      const float2 peer = *reinterpret_cast<const float2*>(smem + SM_XB + tid * 8);
      const float gt = bf16r((c & 1) ? peer.x + sg : sg + peer.x);
      const float up = bf16r((c & 1) ? peer.y + su : su + peer.y);
      const float inner = 0.7978845608028654f * (gt + 0.044715f * gt * gt * gt);
      const float ge = bf16r(gt * rcp(1.0f + ex2(-2.0f * kLog2e * inner)));
      reinterpret_cast<__nv_bfloat16*>(smem + SM_ACT)[b * 64 + col] = __float2bfloat16_rn(ge * up);
    }
    cbar();
    uint32_t bfr[8];
#pragma unroll
    for (int s = 0; s < 8; ++s) bfr[s] = lds32(sb + SM_ACT + (g & 1) * 128 + t * 4 + s * 16);
#pragma unroll
    for (int j = 0; j < 2; ++j) {
      float acc[4][4] = {};
      mbar_wait(full0 + 32 * cs.slot + 8 * warp, cs.par);
      gemv_box64(acc, sb + cs.slot * kStage + warp * kUnit, bfr, lane);
      ll_send64<kFB>(g_s.part, 512 * (c & 1) + 256 * j + 64 * warp, c >> 1, acc, tag | 4u, g, t);
      cs.next();
    }
  }
  {
    if (warp == 0) {
#pragma unroll 1
      for (int it = 0; !__all_sync(0xffffffffu, lane >= 16 || (hown & 7u) == tag); ++it) {
        if (lane < 16) hown = ld_ll1(hown_p);
        if (it > kSpinLimit) __trap();
      }
    }
    const float d = ll_reduce<kFB>(obox, tag | 4u, reinterpret_cast<float*>(smem + SM_RED2), tid);
    if (tid < 16) out[(tid & 1) * kD + 8 * c + (tid >> 1)] = __float2bfloat16_rn(untag16(hown) + bf16r(d));
    if (c == 0 && tid == 0) { g_s.ticket = 0; g_s.hcnt = 0; g_s.tagprev = tag; }
  }
}

typedef CUresult (*EncodeTiledFn)(CUtensorMap*, CUtensorMapDataType, cuuint32_t, void*, const cuuint64_t*,
                                  const cuuint64_t*, const cuuint32_t*, const cuuint32_t*, CUtensorMapInterleave,
                                  CUtensorMapSwizzle, CUtensorMapL2promotion, CUtensorMapFloatOOBfill);

void make_map(EncodeTiledFn enc, CUtensorMap* m, const void* base, uint64_t cols, uint64_t rows, uint32_t box_cols,
              uint32_t box_rows, CUtensorMapSwizzle sw, CUtensorMapL2promotion promo) {
  cuuint64_t dims[2] = {cols, rows};
  cuuint64_t strides[1] = {cols * 2};
  cuuint32_t box[2] = {box_cols, box_rows};
  cuuint32_t es[2] = {1, 1};
  enc(m, CU_TENSOR_MAP_DATA_TYPE_BFLOAT16, 2, const_cast<void*>(base), dims, strides, box, es,
      CU_TENSOR_MAP_INTERLEAVE_NONE, sw, promo, CU_TENSOR_MAP_FLOAT_OOB_FILL_NONE);
}

}

extern "C" void kernel_launch(void* const* d_in, const int* in_sizes, int n_in, void* d_out, int out_size) {
  (void)in_sizes; (void)n_in; (void)out_size;
  static EncodeTiledFn enc = nullptr;
  if (!enc) {
    void* fn = nullptr;
    cudaDriverEntryPointQueryResult qr;
    cudaGetDriverEntryPoint("cuTensorMapEncodeTiled", &fn, cudaEnableDefault, &qr);
    enc = reinterpret_cast<EncodeTiledFn>(fn);
    cudaFuncSetAttribute(fused_decode_kernel, cudaFuncAttributeMaxDynamicSharedMemorySize, kSmemBytes);
  }
  const __nv_bfloat16* x = static_cast<const __nv_bfloat16*>(d_in[0]);
  const __nv_bfloat16* kc = static_cast<const __nv_bfloat16*>(d_in[1]);
  const __nv_bfloat16* vc = static_cast<const __nv_bfloat16*>(d_in[2]);
  CUtensorMap mq, mo, mg, mu, md;
  make_map(enc, &mq, d_in[3], kH * kDH, kD, 64, 64, CU_TENSOR_MAP_SWIZZLE_128B, CU_TENSOR_MAP_L2_PROMOTION_L2_256B);
  make_map(enc, &mo, d_in[4], kD, kH * kDH, 64, 64, CU_TENSOR_MAP_SWIZZLE_128B, CU_TENSOR_MAP_L2_PROMOTION_L2_256B);
  make_map(enc, &mg, d_in[6], kF, kD, 64, 64, CU_TENSOR_MAP_SWIZZLE_128B, CU_TENSOR_MAP_L2_PROMOTION_L2_256B);
  make_map(enc, &mu, d_in[7], kF, kD, 64, 64, CU_TENSOR_MAP_SWIZZLE_128B, CU_TENSOR_MAP_L2_PROMOTION_L2_256B);
  make_map(enc, &md, d_in[8], kD, kF, 64, 64, CU_TENSOR_MAP_SWIZZLE_128B, CU_TENSOR_MAP_L2_PROMOTION_L2_256B);
  fused_decode_kernel<<<kG, kThreads, kSmemBytes, cudaStreamPerThread>>>(
      mq, mo, mg, mu, md, x, kc, vc, static_cast<__nv_bfloat16*>(d_out));
}
```
